```python
import torch

def _softmax(x, axis=-1):
    return torch.softmax(x, dim=axis)
def _gelu(x):
    return torch.nn.functional.gelu(x, approximate="tanh")
def _silu(x):
    return torch.nn.functional.silu(x)
def _sigmoid(x):
    return torch.sigmoid(x)
def _layernorm(x, axis=-1, eps=1e-5):
    m = x.mean(dim=axis, keepdim=True)
    v = x.var(dim=axis, keepdim=True, unbiased=False)
    return (x - m) / torch.sqrt(v + eps)
def _scatter_add(tgt, idx, src, axis=0):
    return tgt.clone().index_add_(axis, idx, src)
def _segment_sum(src, seg, n):
    out = torch.zeros((n,) + src.shape[1:], dtype=src.dtype)
    return out.index_add_(0, seg, src)
def _pad(x, pw):
    flat = tuple(v for pair in reversed(pw) for v in pair)
    return torch.nn.functional.pad(x, flat)

kernel_name = 'gated_mix__gqa_block_cached__glu_gated_geglu__decode'

def setup_inputs():

    _w = (lambda a: (lambda t: t.to(torch.bfloat16) if t.is_floating_point() else t)(torch.as_tensor(a)))
    def _A_setup():
        B, Sq, D = 2, 1, 512
        Hq, Hkv, Sk, Dh = 32, 32, 16384, 128
        assert Hq % Hkv == 0, (Hq, Hkv)
        return {
            "x": _w((lambda *s: torch.randn(*s, dtype=torch.bfloat16) * 0.05)(B, Sq, D)),
            "k_cache": _w((lambda *s: torch.randn(*s, dtype=torch.bfloat16) * 3.2)(B, Hkv, Sk, Dh)),
            "v_cache": _w((lambda *s: torch.randn(*s, dtype=torch.bfloat16) * 0.05)(B, Hkv, Sk, Dh)),
            "wq": _w((lambda *s: torch.randn(*s, dtype=torch.bfloat16) * 3.2)(D, Hq * Dh) * (D ** -0.5)),
            "wo": _w((lambda *s: torch.randn(*s, dtype=torch.bfloat16) * 0.05)(Hq * Dh, D) * ((Hq * Dh) ** -0.5)),
        }
    _A_in = _A_setup()

    def _B_setup():
        B, S, Dm, Df = 2, 1, 512, 1376
        return {
            "x": _w((lambda *s: torch.randn(*s, dtype=torch.bfloat16) * 0.05)(B, S, Dm)),
            "w_gate": _w((lambda *s: torch.randn(*s, dtype=torch.bfloat16) * 0.2)(Dm, Df) * (Dm ** -0.5)),
            "w_up": _w((lambda *s: torch.randn(*s, dtype=torch.bfloat16) * 0.2)(Dm, Df) * (Dm ** -0.5)),
            "w_down": _w((lambda *s: torch.randn(*s, dtype=torch.bfloat16) * 0.2)(Df, Dm) * (Df ** -0.5)),
        }
    _B_in = _B_setup()

    return {
        "A_x": _A_in["x"],
        "A_k_cache": _A_in["k_cache"],
        "A_v_cache": _A_in["v_cache"],
        "A_wq": _A_in["wq"],
        "A_wo": _A_in["wo"],
        "B_x": _B_in["x"],
        "B_w_gate": _B_in["w_gate"],
        "B_w_up": _B_in["w_up"],
        "B_w_down": _B_in["w_down"],
        "gate_w": _w((lambda *s: torch.randn(*s, dtype=torch.bfloat16) * 0.05)(512) * 16.0),
    }

def reference(A_x, A_k_cache, A_v_cache, A_wq, A_wo, B_x, B_w_gate, B_w_up, B_w_down, gate_w):
    def _A_ref(x, k_cache, v_cache, wq, wo):
        B, Sq, D = x.shape
        Hq, Dh = 32, 128
        Hkv = k_cache.shape[1]
        rep = Hq // Hkv
        q = (lambda x, *d: x.permute(*d))((x @ wq).reshape(B, Sq, Hq, Dh), 0, 2, 1, 3)
        k = (lambda x, n, axis: torch.repeat_interleave(x, n, dim=axis))(k_cache, rep, axis=1)
        v = (lambda x, n, axis: torch.repeat_interleave(x, n, dim=axis))(v_cache, rep, axis=1)
        scores = torch.einsum("bhqd,bhkd->bhqk", q, k) * (Dh ** -0.5)
        p = _softmax(scores, axis=-1)
        o = torch.einsum("bhqk,bhkd->bhqd", p, v)
        return (lambda x, *d: x.permute(*d))(o, 0, 2, 1, 3).reshape(B, Sq, Hq * Dh) @ wo

    def _B_ref(x, w_gate, w_up, w_down):
        g = torch.einsum("bsd,df->bsf", x, w_gate)
        u = torch.einsum("bsd,df->bsf", x, w_up)
        h = _gelu(g) * u
        return torch.einsum("bsf,fd->bsd", h, w_down)

    x = A_x
    g = _sigmoid((x * gate_w).sum(-1, keepdims=True))
    a = _A_ref(x, A_k_cache, A_v_cache, A_wq, A_wo)
    b = _B_ref(x, B_w_gate, B_w_up, B_w_down)
    return g * a + (1 - g) * b
```

```cpp
#include <cuda_runtime.h>
#include <cuda_bf16.h>
#include <stdint.h>

#define P_NST 10
#define P_D 3
#define P_DF 2
#define P_RK 0
#define P_YCLR 1
#define P_SPEC 62
#define P_FIN 4
#define P_PREFETCH 0

namespace {

constexpr int NCTA = 132;
constexpr int NST = P_NST;
constexpr int FIN = P_FIN;
constexpr int UPH = 256;
constexpr int SW = UPH - 2 * FIN;
constexpr int NBH = 64;
constexpr int SWU = NBH * SW;
constexpr int DEPTH = P_D;
constexpr int NSLOT = NST / 2;
constexpr int NSTATIC = (DEPTH + 1) / 2 < 2 ? 2 : (DEPTH + 1) / 2;
constexpr unsigned GRABS = SWU - NSTATIC * NCTA + NCTA;
constexpr int TILE = 16384;
constexpr int NTHR = 448;
constexpr int NGLU = 43;
constexpr int GLU0 = NCTA - NGLU;
constexpr int DF = 1376;

constexpr int SM_Q = NST * TILE;
constexpr int SM_FL = SM_Q + 16384;
constexpr int SM_XS = SM_FL + 2 * 4 * 528;
constexpr int SM_XS2 = SM_XS + 8 * 272;
constexpr int SM_RED = SM_XS2 + 8 * 272;
constexpr int SM_H = SM_RED + 4096;
constexpr int SM_BAR = SM_H + 256;
constexpr int B_FULL = SM_BAR;
constexpr int B_EMPTY = B_FULL + 8 * NST;
constexpr int B_FLF = B_EMPTY + 8 * NST;
constexpr int B_FLE = B_FLF + 16;
constexpr int B_Q0 = B_FLE + 16;
constexpr int B_Q1 = B_Q0 + 8;
constexpr int B_X = B_Q1 + 8;
constexpr int B_W = B_X + 8;
constexpr int B_W2 = B_W + 8;
constexpr int SM_INFO = B_W2 + 8;
constexpr int SM_EPOCH = SM_INFO + 4 * 8;
constexpr int SM_TOTAL0 = SM_EPOCH + 16;
constexpr int SM_TOTAL = SM_TOTAL0 < 118 * 1024 ? 118 * 1024 : SM_TOTAL0;

constexpr unsigned INF_FINAL = 0x100u;
constexpr unsigned INF_END = 0x200u;

__device__ unsigned g_epoch[32];
__device__ unsigned g_grab[32];
__device__ __align__(128) unsigned long long g_qbuf[4096];
__device__ __align__(128) uint2 g_part[NBH * NCTA * 32];
__device__ __align__(128) uint4 g_hdr[NBH * NCTA * 2];
__device__ __align__(128) unsigned long long g_gbuf[NGLU * 1024];
__device__ __align__(128) unsigned long long g_ybuf[32 * 1024];
#define TS(i) do {} while (0)

constexpr long long SPIN_LIMIT = 2000000000ll;

__device__ __forceinline__ void mbar_init(uint32_t bar, uint32_t cnt) {
  asm volatile("mbarrier.init.shared::cta.b64 [%0], %1;" ::"r"(bar), "r"(cnt) : "memory");
}
__device__ __forceinline__ void mbar_expect_tx(uint32_t bar, uint32_t bytes) {
  asm volatile("mbarrier.arrive.expect_tx.shared::cta.b64 _, [%0], %1;" ::"r"(bar), "r"(bytes) : "memory");
}
__device__ __forceinline__ void mbar_arrive(uint32_t bar) {
  asm volatile("mbarrier.arrive.shared::cta.b64 _, [%0];" ::"r"(bar) : "memory");
}
__device__ __forceinline__ bool mbar_try(uint32_t bar, uint32_t parity) {
  uint32_t ok;
  asm volatile("{\n.reg .pred p;\nmbarrier.try_wait.parity.shared::cta.b64 p, [%1], %2;\nselp.u32 %0, 1, 0, p;\n}\n"
               : "=r"(ok) : "r"(bar), "r"(parity) : "memory");
  return ok != 0;
}
__device__ __forceinline__ void mbar_wait(uint32_t bar, uint32_t parity) {
  if (mbar_try(bar, parity)) return;
  long long t0 = clock64();
  while (!mbar_try(bar, parity)) {
    if (clock64() - t0 > SPIN_LIMIT) __trap();
  }
}
__device__ __forceinline__ bool mbar_try_cluster(uint32_t bar, uint32_t parity) {
  uint32_t ok;
  asm volatile("{\n.reg .pred p;\nmbarrier.try_wait.parity.acquire.cluster.shared::cta.b64 p, [%1], %2;\nselp.u32 %0, 1, 0, p;\n}\n"
               : "=r"(ok) : "r"(bar), "r"(parity) : "memory");
  return ok != 0;
}
__device__ __forceinline__ void mbar_wait_cluster(uint32_t bar, uint32_t parity) {
  if (mbar_try_cluster(bar, parity)) return;
  long long t0 = clock64();
  while (!mbar_try_cluster(bar, parity)) {
    if (clock64() - t0 > SPIN_LIMIT) __trap();
  }
}
__device__ __forceinline__ void bulk_load(uint32_t dst, const void* src, uint32_t bytes, uint32_t bar, uint64_t pol) {
  asm volatile("cp.async.bulk.shared::cluster.global.mbarrier::complete_tx::bytes.L2::cache_hint [%0], [%1], %2, [%3], %4;"
               ::"r"(dst), "l"(src), "r"(bytes), "r"(bar), "l"(pol) : "memory");
}
__device__ __forceinline__ void bulk_prefetch(const void* src, uint32_t bytes) {
  asm volatile("cp.async.bulk.prefetch.L2.global [%0], %1;" ::"l"(src), "r"(bytes) : "memory");
}
__device__ __forceinline__ void ldsm4(uint32_t addr, uint32_t& a0, uint32_t& a1, uint32_t& a2, uint32_t& a3) {
  asm volatile("ldmatrix.sync.aligned.m8n8.x4.shared.b16 {%0,%1,%2,%3}, [%4];"
               : "=r"(a0), "=r"(a1), "=r"(a2), "=r"(a3) : "r"(addr) : "memory");
}
__device__ __forceinline__ void ldsm4t(uint32_t addr, uint32_t& a0, uint32_t& a1, uint32_t& a2, uint32_t& a3) {
  asm volatile("ldmatrix.sync.aligned.m8n8.x4.trans.shared.b16 {%0,%1,%2,%3}, [%4];"
               : "=r"(a0), "=r"(a1), "=r"(a2), "=r"(a3) : "r"(addr) : "memory");
}
__device__ __forceinline__ void mma16816(float (&c)[4], uint32_t a0, uint32_t a1, uint32_t a2, uint32_t a3, uint32_t b0, uint32_t b1) {
  asm volatile("mma.sync.aligned.m16n8k16.row.col.f32.bf16.bf16.f32 {%0,%1,%2,%3}, {%4,%5,%6,%7}, {%8,%9}, {%0,%1,%2,%3};"
               : "+f"(c[0]), "+f"(c[1]), "+f"(c[2]), "+f"(c[3]) : "r"(a0), "r"(a1), "r"(a2), "r"(a3), "r"(b0), "r"(b1));
}
__device__ __forceinline__ uint32_t lds32(uint32_t a) { uint32_t v; asm volatile("ld.shared.b32 %0, [%1];" : "=r"(v) : "r"(a) : "memory"); return v; }
__device__ __forceinline__ uint32_t lds32v(uint32_t a) { uint32_t v; asm volatile("ld.volatile.shared.b32 %0, [%1];" : "=r"(v) : "r"(a) : "memory"); return v; }
__device__ __forceinline__ float2 lds64f(uint32_t a) { float2 v; asm volatile("ld.shared.v2.f32 {%0,%1}, [%2];" : "=f"(v.x), "=f"(v.y) : "r"(a) : "memory"); return v; }
__device__ __forceinline__ uint4 lds128(uint32_t a) { uint4 v; asm volatile("ld.shared.v4.b32 {%0,%1,%2,%3}, [%4];" : "=r"(v.x), "=r"(v.y), "=r"(v.z), "=r"(v.w) : "r"(a) : "memory"); return v; }
__device__ __forceinline__ void sts32(uint32_t a, uint32_t v) { asm volatile("st.shared.b32 [%0], %1;" ::"r"(a), "r"(v) : "memory"); }
__device__ __forceinline__ void sts32v(uint32_t a, uint32_t v) { asm volatile("st.volatile.shared.b32 [%0], %1;" ::"r"(a), "r"(v) : "memory"); }
__device__ __forceinline__ void sts64(uint32_t a, uint32_t x, uint32_t y) { asm volatile("st.shared.v2.b32 [%0], {%1,%2};" ::"r"(a), "r"(x), "r"(y) : "memory"); }
__device__ __forceinline__ void sts128(uint32_t a, uint32_t x, uint32_t y, uint32_t z, uint32_t w) { asm volatile("st.shared.v4.b32 [%0], {%1,%2,%3,%4};" ::"r"(a), "r"(x), "r"(y), "r"(z), "r"(w) : "memory"); }
__device__ __forceinline__ uint32_t pack_bf16(float lo, float hi) {
  uint32_t r; asm("cvt.rn.bf16x2.f32 %0, %1, %2;" : "=r"(r) : "f"(hi), "f"(lo)); return r;
}
__device__ __forceinline__ float bf_lo(uint32_t v) { return __uint_as_float(v << 16); }
__device__ __forceinline__ float bf_hi(uint32_t v) { return __uint_as_float(v & 0xffff0000u); }
__device__ __forceinline__ float bf_round(float v) { return __bfloat162float(__float2bfloat16_rn(v)); }
__device__ __forceinline__ float ex2(float v) { float r; asm("ex2.approx.ftz.f32 %0, %1;" : "=f"(r) : "f"(v)); return r; }
__device__ __forceinline__ void aux_bar() { asm volatile("bar.sync 1, 256;" ::: "memory"); }
__device__ __forceinline__ uint4 ldg128(const void* p) {
  uint4 v; asm volatile("ld.global.nc.v4.b32 {%0,%1,%2,%3}, [%4];" : "=r"(v.x), "=r"(v.y), "=r"(v.z), "=r"(v.w) : "l"(p)); return v;
}
__device__ __forceinline__ uint2 ldg64(const void* p) {
  uint2 v; asm volatile("ld.global.nc.v2.b32 {%0,%1}, [%2];" : "=r"(v.x), "=r"(v.y) : "l"(p)); return v;
}
__device__ __forceinline__ uint4 ld_relaxed128(const void* p) {
  unsigned long long a, b;
  asm volatile("ld.relaxed.gpu.global.v2.b64 {%0,%1}, [%2];" : "=l"(a), "=l"(b) : "l"(p) : "memory");
  return make_uint4((uint32_t)a, (uint32_t)(a >> 32), (uint32_t)b, (uint32_t)(b >> 32));
}
__device__ __forceinline__ uint2 ld_relaxed64(const void* p) {
  unsigned long long a;
  asm volatile("ld.relaxed.gpu.global.b64 %0, [%1];" : "=l"(a) : "l"(p) : "memory");
  return make_uint2((uint32_t)a, (uint32_t)(a >> 32));
}
__device__ __forceinline__ void st_relaxed64(void* p, uint32_t lo, uint32_t hi) {
  unsigned long long a = ((unsigned long long)hi << 32) | lo;
  asm volatile("st.relaxed.gpu.global.b64 [%0], %1;" ::"l"(p), "l"(a) : "memory");
}
__device__ __forceinline__ void st_relaxed128(void* p, uint32_t lo0, uint32_t hi0, uint32_t lo1, uint32_t hi1) {
  unsigned long long a = ((unsigned long long)hi0 << 32) | lo0, b = ((unsigned long long)hi1 << 32) | lo1;
  asm volatile("st.relaxed.gpu.global.v2.b64 [%0], {%1,%2};" ::"l"(p), "l"(a), "l"(b) : "memory");
}
__device__ __forceinline__ uint4 ldcg128(const void* p) {
  uint4 v; asm volatile("ld.global.cg.v4.b32 {%0,%1,%2,%3}, [%4];" : "=r"(v.x), "=r"(v.y), "=r"(v.z), "=r"(v.w) : "l"(p) : "memory"); return v;
}
__device__ __forceinline__ void st_async64(uint32_t addr, uint32_t x, uint32_t y, uint32_t bar) {
  asm volatile("st.async.shared::cluster.mbarrier::complete_tx::bytes.v2.b32 [%0], {%1,%2}, [%3];" ::"r"(addr), "r"(x), "r"(y), "r"(bar) : "memory");
}
__device__ __forceinline__ uint32_t mapa(uint32_t addr, uint32_t rank) {
  uint32_t r; asm("mapa.shared::cluster.u32 %0, %1, %2;" : "=r"(r) : "r"(addr), "r"(rank)); return r;
}

__device__ __forceinline__ void gemv32_reduce(const uint4 (&w)[8], const uint4& x0, const uint4& x1, uint32_t red, int warp, int lane) {
  float a0[8], a1[8];
#pragma unroll
  for (int j = 0; j < 8; j++) { a0[j] = 0.f; a1[j] = 0.f; }
  const uint32_t xa[4] = {x0.x, x0.y, x0.z, x0.w}, xb[4] = {x1.x, x1.y, x1.z, x1.w};
#pragma unroll
  for (int j = 0; j < 8; j++) {
    const float fa = (j & 1) ? bf_hi(xa[j >> 1]) : bf_lo(xa[j >> 1]);
    const float fb = (j & 1) ? bf_hi(xb[j >> 1]) : bf_lo(xb[j >> 1]);
    const uint32_t ww[4] = {w[j].x, w[j].y, w[j].z, w[j].w};
#pragma unroll
    for (int i = 0; i < 4; i++) {
      const float lo = bf_lo(ww[i]), hi = bf_hi(ww[i]);
      a0[2 * i] = fmaf(fa, lo, a0[2 * i]); a0[2 * i + 1] = fmaf(fa, hi, a0[2 * i + 1]);
      a1[2 * i] = fmaf(fb, lo, a1[2 * i]); a1[2 * i + 1] = fmaf(fb, hi, a1[2 * i + 1]);
    }
  }
  const bool b4 = lane & 16, b3 = lane & 8, b2 = lane & 4;
  float v[8];
#pragma unroll
  for (int j = 0; j < 8; j++) v[j] = (b4 ? a1[j] : a0[j]) + __shfl_xor_sync(~0u, b4 ? a0[j] : a1[j], 16);
  float u[4];
#pragma unroll
  for (int j = 0; j < 4; j++) u[j] = (b3 ? v[j + 4] : v[j]) + __shfl_xor_sync(~0u, b3 ? v[j] : v[j + 4], 8);
  const float r0 = (b2 ? u[2] : u[0]) + __shfl_xor_sync(~0u, b2 ? u[0] : u[2], 4);
  const float r1 = (b2 ? u[3] : u[1]) + __shfl_xor_sync(~0u, b2 ? u[1] : u[3], 4);
  const int idx = (b4 ? 32 : 0) + (lane & 3) * 8 + (b3 ? 4 : 0) + (b2 ? 2 : 0);
  sts64(red + (warp * 64 + idx) * 4, __float_as_uint(r0), __float_as_uint(r1));
}
__device__ __forceinline__ float2 gemv32_final(uint32_t red, int i  ) {
  float2 s = make_float2(0.f, 0.f);
#pragma unroll
  for (int w = 0; w < 8; w++) { float2 v = lds64f(red + (w * 64 + 2 * i) * 4); s.x += v.x; s.y += v.y; }
  return s;
}

__device__ __forceinline__ void wo_mma(const uint32_t (&A)[8][8], uint32_t slot, int g, int t, float (&c)[4][4]) {
  uint4 bv[4];
#pragma unroll
  for (int j = 0; j < 4; j++) bv[j] = lds128(slot + g * 272 + t * 64 + ((j ^ ((t >> 1) << 1)) << 4));
#pragma unroll
  for (int i = 0; i < 4; i++) { c[i][0] = 0.f; c[i][1] = 0.f; c[i][2] = 0.f; c[i][3] = 0.f; }
#pragma unroll
  for (int j = 0; j < 4; j++) {
    mma16816(c[0], A[2 * j][0], A[2 * j][1], A[2 * j][2], A[2 * j][3], bv[j].x, bv[j].y);
    mma16816(c[1], A[2 * j][4], A[2 * j][5], A[2 * j][6], A[2 * j][7], bv[j].x, bv[j].y);
    mma16816(c[2], A[2 * j + 1][0], A[2 * j + 1][1], A[2 * j + 1][2], A[2 * j + 1][3], bv[j].z, bv[j].w);
    mma16816(c[3], A[2 * j + 1][4], A[2 * j + 1][5], A[2 * j + 1][6], A[2 * j + 1][7], bv[j].z, bv[j].w);
  }
}
__device__ __forceinline__ float wo_reduce(const float (&c)[4][4], float w0, float w1, int t) {
  const float y0 = w0 * (c[0][0] + c[2][0]) + w1 * (c[0][1] + c[2][1]);
  const float y1 = w0 * (c[0][2] + c[2][2]) + w1 * (c[0][3] + c[2][3]);
  const float y2 = w0 * (c[1][0] + c[3][0]) + w1 * (c[1][1] + c[3][1]);
  const float y3 = w0 * (c[1][2] + c[3][2]) + w1 * (c[1][3] + c[3][3]);
  const bool b1 = t & 2, b0 = t & 1;
  const float z0 = (b1 ? y2 : y0) + __shfl_xor_sync(~0u, b1 ? y0 : y2, 2);
  const float z1 = (b1 ? y3 : y1) + __shfl_xor_sync(~0u, b1 ? y1 : y3, 2);
  return (b0 ? z1 : z0) + __shfl_xor_sync(~0u, b0 ? z0 : z1, 1);
}

__global__ void __cluster_dims__(2, 1, 1) __launch_bounds__(NTHR, 1)
fused_decode_kernel(const __nv_bfloat16* __restrict__ x, const char* __restrict__ Kc, const char* __restrict__ Vc,
                    const __nv_bfloat16* __restrict__ wq, const __nv_bfloat16* __restrict__ wo,
                    const __nv_bfloat16* __restrict__ wg, const __nv_bfloat16* __restrict__ wu,
                    const __nv_bfloat16* __restrict__ wd, const __nv_bfloat16* __restrict__ gw,
                    __nv_bfloat16* __restrict__ out) {
  extern __shared__ __align__(1024) unsigned char smem_raw[];
  const uint32_t sb = (uint32_t)__cvta_generic_to_shared(smem_raw);
  const int tid = threadIdx.x, warp = tid >> 5, lane = tid & 31;
  const int cta = blockIdx.x;
  const bool owner = cta < 128;

  if (warp >= 6) {
    const int at = tid - 192, aw = warp - 6;
    const int g = lane >> 2, t = lane & 3;
    uint4 w[8];
    const int rg = at >> 2, cq = at & 3;
    if (owner) {
#pragma unroll
      for (int j = 0; j < 8; j++) w[j] = ldg128(wq + (size_t)(rg * 8 + j) * 4096 + cta * 32 + cq * 8);
    }
    const uint4 x0 = ldg128(x + rg * 8), x1 = ldg128(x + 512 + rg * 8);
    asm volatile("barrier.cluster.arrive.release.aligned;\nbarrier.cluster.wait.acquire.aligned;" ::: "memory");
    const uint32_t tag = lds32(sb + SM_EPOCH) + 1u;
    if (owner) {
      gemv32_reduce(w, x0, x1, sb + SM_RED, aw, lane);
      aux_bar();
      if (at < 32) {
        const float2 s = gemv32_final(sb + SM_RED, at);
        st_relaxed64(&g_qbuf[(at >> 4) * 2048 + cta * 16 + (at & 15)], pack_bf16(s.x, s.y), tag);
      }
    }
    if (at == 0) TS(1);
    if (at < 64) {
      long long t0 = clock64();
      uint4 v = ld_relaxed128(&g_qbuf[at * 2]);
      while (v.y != tag || v.w != tag) {
        if (clock64() - t0 > SPIN_LIMIT) __trap();
        v = ld_relaxed128(&g_qbuf[at * 2]);
      }
      sts64(sb + SM_Q + at * 8, v.x, v.z);
      __syncwarp();
      if (lane == 0) mbar_arrive(sb + B_Q0);
    }
    if (at == 0) TS(2);
    aux_bar();
    {
      uint4 v[8];
#pragma unroll
      for (int j = 0; j < 8; j++) v[j] = ld_relaxed128(&g_qbuf[(j * 256 + at) * 2]);
      long long t0 = clock64();
#pragma unroll
      for (int j = 0; j < 8; j++) {
        while (v[j].y != tag || v[j].w != tag) {
          if (clock64() - t0 > SPIN_LIMIT) __trap();
          v[j] = ld_relaxed128(&g_qbuf[(j * 256 + at) * 2]);
        }
        if (j > 0 || at >= 64) sts64(sb + SM_Q + (j * 256 + at) * 8, v[j].x, v[j].z);
      }
      __syncwarp();
      if (lane == 0) mbar_arrive(sb + B_Q1);
    }
    if (at == 0) TS(3);
    if (cta >= GLU0) {
      const int f = cta - GLU0;
      uint4 w2[8];
#pragma unroll
      for (int j = 0; j < 8; j++) w[j] = ldg128(wg + (size_t)(rg * 8 + j) * DF + f * 32 + cq * 8);
#pragma unroll
      for (int j = 0; j < 8; j++) w2[j] = ldg128(wu + (size_t)(rg * 8 + j) * DF + f * 32 + cq * 8);
      gemv32_reduce(w, x0, x1, sb + SM_RED, aw, lane);
      const int dr = lane >> 3, dc = aw * 64 + (lane & 7) * 8;
#pragma unroll
      for (int j = 0; j < 8; j++) w[j] = ldg128(wd + (size_t)(f * 32 + dr * 8 + j) * 512 + dc);
      gemv32_reduce(w2, x0, x1, sb + SM_RED + 2048, aw, lane);
      aux_bar();
      if (at < 32) {
        const float2 gs = gemv32_final(sb + SM_RED, at), us = gemv32_final(sb + SM_RED + 2048, at);
        float hh[2];
#pragma unroll
        for (int i = 0; i < 2; i++) {
          const float gv = bf_round(i ? gs.y : gs.x), uv = bf_round(i ? us.y : us.x);
          const float inner = 0.7978845608028654f * (gv + 0.044715f * gv * gv * gv);
          const float ge = bf_round(0.5f * gv * (1.f + tanhf(inner)));
          hh[i] = bf_round(ge * uv);
        }
        sts64(sb + SM_H + at * 8, __float_as_uint(hh[0]), __float_as_uint(hh[1]));
      }
      aux_bar();
      float a0[8], a1[8];
#pragma unroll
      for (int j = 0; j < 8; j++) { a0[j] = 0.f; a1[j] = 0.f; }
#pragma unroll
      for (int j = 0; j < 8; j++) {
        const float fa = __uint_as_float(lds32(sb + SM_H + (dr * 8 + j) * 4));
        const float fb = __uint_as_float(lds32(sb + SM_H + (32 + dr * 8 + j) * 4));
        const uint32_t ww[4] = {w[j].x, w[j].y, w[j].z, w[j].w};
#pragma unroll
        for (int i = 0; i < 4; i++) {
          const float lo = bf_lo(ww[i]), hi = bf_hi(ww[i]);
          a0[2 * i] = fmaf(fa, lo, a0[2 * i]); a0[2 * i + 1] = fmaf(fa, hi, a0[2 * i + 1]);
          a1[2 * i] = fmaf(fb, lo, a1[2 * i]); a1[2 * i + 1] = fmaf(fb, hi, a1[2 * i + 1]);
        }
      }
      const bool b4 = lane & 16, b3 = lane & 8;
      float v[8], u[4];
#pragma unroll
      for (int j = 0; j < 8; j++) v[j] = (b4 ? a1[j] : a0[j]) + __shfl_xor_sync(~0u, b4 ? a0[j] : a1[j], 16);
#pragma unroll
      for (int j = 0; j < 4; j++) u[j] = (b3 ? v[j + 4] : v[j]) + __shfl_xor_sync(~0u, b3 ? v[j] : v[j + 4], 8);
      unsigned long long* dst = &g_gbuf[f * 1024 + (b4 ? 512 : 0) + dc + (b3 ? 4 : 0)];
      st_relaxed128(dst, __float_as_uint(u[0]), tag, __float_as_uint(u[1]), tag);
      st_relaxed128(dst + 2, __float_as_uint(u[2]), tag, __float_as_uint(u[3]), tag);
    }
    if (!owner) return;
    const int bh = cta >> 1, r = cta & 1, h = bh & 31, b = bh >> 5;
    const int n0 = 256 * r + 32 * aw;
    uint32_t A[8][8];
#pragma unroll
    for (int ks = 0; ks < 8; ks++) {
      const int L = 8 * t + (ks ^ ((t >> 1) << 2));
      const int d0 = 16 * (L & 3) + (L >> 2);
      const __nv_bfloat16* p = wo + (size_t)(h * 128 + d0) * 512 + n0 + 4 * g;
      const uint2 v0 = ldg64(p), v1 = ldg64(p + 8 * 512), v2 = ldg64(p + 64 * 512), v3 = ldg64(p + 72 * 512);
      A[ks][0] = __byte_perm(v0.x, v1.x, 0x5410); A[ks][1] = __byte_perm(v0.x, v1.x, 0x7632);
      A[ks][2] = __byte_perm(v2.x, v3.x, 0x5410); A[ks][3] = __byte_perm(v2.x, v3.x, 0x7632);
      A[ks][4] = __byte_perm(v0.y, v1.y, 0x5410); A[ks][5] = __byte_perm(v0.y, v1.y, 0x7632);
      A[ks][6] = __byte_perm(v2.y, v3.y, 0x5410); A[ks][7] = __byte_perm(v2.y, v3.y, 0x7632);
    }
    const int oi = cta * 8 + aw;
    float gate, gluterm;
    {
      const int ob = oi >> 9;
      float s = 0.f;
#pragma unroll
      for (int j = 0; j < 2; j++) {
        const uint4 xv = ldg128(x + ob * 512 + j * 256 + lane * 8), gv = ldg128(gw + j * 256 + lane * 8);
        const uint32_t xx[4] = {xv.x, xv.y, xv.z, xv.w}, gg[4] = {gv.x, gv.y, gv.z, gv.w};
#pragma unroll
        for (int i = 0; i < 4; i++) s += bf_round(bf_lo(xx[i]) * bf_lo(gg[i])) + bf_round(bf_hi(xx[i]) * bf_hi(gg[i]));
      }
      if (P_YCLR) st_relaxed64(&g_ybuf[h * 1024 + b * 512 + n0 + lane], 0u, tag - 1u);
      mbar_wait(sb + B_W2, 0);
      float bs = 0.f;
      long long t0 = clock64();
#pragma unroll
      for (int j = 0; j < 2; j++) {
        const int f = j * 32 + lane;
        if (f < NGLU) {
          uint2 v = ld_relaxed64(&g_gbuf[f * 1024 + oi]);
          while (v.y != tag) {
            if (clock64() - t0 > SPIN_LIMIT) __trap();
            __nanosleep(200);
            v = ld_relaxed64(&g_gbuf[f * 1024 + oi]);
          }
          bs += __uint_as_float(v.x);
        }
      }
#pragma unroll
      for (int o = 16; o > 0; o >>= 1) { s += __shfl_xor_sync(~0u, s, o); bs += __shfl_xor_sync(~0u, bs, o); }
      s = bf_round(s);
      gate = bf_round(1.f / (1.f + expf(-s)));
      gluterm = bf_round(bf_round(1.f - gate) * bf_round(bs));
    }
    if (at == 0) TS(4);
    mbar_wait(sb + B_W, 0);
    float Ms, Ls, ysw;
    {
      const int pg = at >> 4, c16 = at & 15;
      uint4 hd[5], pv[9];
      const uint2* part = g_part + (size_t)bh * (NCTA * 32);
      const uint32_t par = tag & 1u;
      bool ldd = bh >= P_SPEC;
      long long t0 = clock64();
      while (true) {
#pragma unroll
        for (int k = 0; k < 5; k++) {
          const int i = k * 32 + lane;
          hd[k] = make_uint4(0, ~tag, 0, 0);
          if (i < NCTA) hd[k] = ld_relaxed128(&g_hdr[(bh * NCTA + i) * 2]);
        }
#pragma unroll
        for (int k = 0; k < 9; k++) {
          const int i = k * 16 + pg;
          pv[k] = make_uint4(~par, 0, 0, 0);
          if (i < NCTA && ldd) pv[k] = ld_relaxed128(part + i * 32 + c16 * 2);
        }
        unsigned cnt = 0;
        bool bad = false;
#pragma unroll
        for (int k = 0; k < 5; k++) {
          const bool ok = hd[k].y == tag && (hd[k].w >> 8) == (tag & 0xffffffu);
          if (ok) cnt += hd[k].w & 0xffu;
          hd[k].y = ok;
          const unsigned vm = __ballot_sync(~0u, ok) >> pg;
          if ((vm & 1u) && (((pv[2 * k].x ^ par) | (pv[2 * k].z ^ par)) & 1u)) bad = true;
          if (k < 4 && (vm & 0x10000u) && (((pv[2 * k + 1].x ^ par) | (pv[2 * k + 1].z ^ par)) & 1u)) bad = true;
        }
        cnt = __reduce_add_sync(~0u, cnt + (bad ? 0x10000u : 0u));
        if (cnt == (unsigned)SW) break;
        if ((cnt & 0xffffu) == (unsigned)SW) ldd = true;
        if (clock64() - t0 > SPIN_LIMIT) __trap();
      }
      if (at == 0) { TS(5); if (cta == 0) asm volatile("st.relaxed.gpu.global.u32 [%0], %1;" ::"l"(&g_epoch[0]), "r"(tag) : "memory"); }
      float m = -INFINITY;
#pragma unroll
      for (int k = 0; k < 5; k++) if (hd[k].y) m = fmaxf(m, __uint_as_float(hd[k].x));
#pragma unroll
      for (int o = 16; o > 0; o >>= 1) m = fmaxf(m, __shfl_xor_sync(~0u, m, o));
      float e[5], l = 0.f;
#pragma unroll
      for (int k = 0; k < 5; k++) {
        const bool ok = hd[k].y;
        e[k] = ok ? ex2(__uint_as_float(hd[k].x) - m) : -1.f;
        if (ok) l = fmaf(e[k], __uint_as_float(hd[k].z), l);
      }
#pragma unroll
      for (int o = 16; o > 0; o >>= 1) l += __shfl_xor_sync(~0u, l, o);
      Ms = m; Ls = l;
      float acc[8];
#pragma unroll
      for (int j = 0; j < 8; j++) acc[j] = 0.f;
#pragma unroll
      for (int k = 0; k < 9; k++) {
        const float wk = __shfl_sync(~0u, e[k >> 1], pg + 16 * (k & 1));
        if (wk >= 0.f) {
          const uint32_t pp[4] = {pv[k].x, pv[k].y, pv[k].z, pv[k].w};
#pragma unroll
          for (int i = 0; i < 4; i++) {
            acc[2 * i] = fmaf(wk, bf_lo(pp[i]), acc[2 * i]);
            acc[2 * i + 1] = fmaf(wk, bf_hi(pp[i]), acc[2 * i + 1]);
          }
        }
      }
#pragma unroll
      for (int j = 0; j < 8; j++) acc[j] += __shfl_xor_sync(~0u, acc[j], 16);
      if (lane < 16)
        sts128(sb + SM_XS2 + aw * 272 + c16 * 16, pack_bf16(acc[0], acc[1]), pack_bf16(acc[2], acc[3]),
               pack_bf16(acc[4], acc[5]), pack_bf16(acc[6], acc[7]));
      aux_bar();
      float c[4][4];
      wo_mma(A, sb + SM_XS2, g, t, c);
      ysw = wo_reduce(c, 1.f, 1.f, t);
    }
    if (at == 0) TS(6);
    mbar_wait_cluster(sb + B_X, 0);
    if (at == 0) TS(7);
    {
      const float2 h0 = lds64f(sb + SM_XS + (2 * t) * 272 + 256), h1 = lds64f(sb + SM_XS + (2 * t + 1) * 272 + 256);
      float c[4][4];
      wo_mma(A, sb + SM_XS, g, t, c);
      float M = fmaxf(fmaxf(h0.x, h1.x), Ms);
      M = fmaxf(M, __shfl_xor_sync(~0u, M, 1));
      M = fmaxf(M, __shfl_xor_sync(~0u, M, 2));
      const float e0 = ex2(h0.x - M), e1 = ex2(h1.x - M), es = ex2(Ms - M);
      float L = e0 * h0.y + e1 * h1.y;
      L += __shfl_xor_sync(~0u, L, 1);
      L += __shfl_xor_sync(~0u, L, 2);
      L = fmaf(es, Ls, L);
      const float y = fmaf(es, ysw, wo_reduce(c, e0, e1, t)) / L;
      st_relaxed64(&g_ybuf[h * 1024 + b * 512 + n0 + lane], __float_as_uint(y), tag);
    }
    if (at == 0) TS(8);
    {
      const unsigned long long* p = &g_ybuf[lane * 1024 + oi];
      uint2 v = ld_relaxed64(p);
      if (v.y != tag) {
        long long t0 = clock64();
        do {
          if (clock64() - t0 > SPIN_LIMIT) __trap();
          v = ld_relaxed64(p);
        } while (v.y != tag);
      }
      float a = __uint_as_float(v.x);
#pragma unroll
      for (int o = 16; o > 0; o >>= 1) a += __shfl_xor_sync(~0u, a, o);
      if (lane == 0) out[oi] = __float2bfloat16_rn(bf_round(gate * bf_round(a)) + gluterm);
    }
    if (at == 0) TS(9);
    return;
  }

  if (warp == 4) {
    uint64_t pol;
    unsigned grab = 0;
    if (lane == 0) {
      TS(0);
      for (int s = 0; s < NST; s++) { mbar_init(sb + B_FULL + 8 * s, 1); mbar_init(sb + B_EMPTY + 8 * s, 4); }
      for (int s = 0; s < 2; s++) { mbar_init(sb + B_FLF + 8 * s, 4); mbar_init(sb + B_FLE + 8 * s, 1); }
      mbar_init(sb + B_Q0, 2); mbar_init(sb + B_Q1, 8); mbar_init(sb + B_X, 1); mbar_init(sb + B_W, 1); mbar_init(sb + B_W2, 1);
      for (int s = 0; s < NSLOT; s++) sts32v(sb + SM_INFO + 4 * s, 0xffffffffu);
      asm volatile("fence.mbarrier_init.release.cluster;" ::: "memory");
      asm volatile("fence.proxy.async.shared::cta;" ::: "memory");
      mbar_expect_tx(sb + B_X, 8 * (256 + 8));
    }
    __syncwarp();
    asm volatile("barrier.cluster.arrive.release.aligned;" ::: "memory");
    if (lane == 0) {
      asm volatile("createpolicy.fractional.L2::evict_first.b64 %0, 1.0;" : "=l"(pol));
#pragma unroll
      for (int n = 0; n < DEPTH; n++) {
        const unsigned u = cta + NCTA * (n >> 1), bh = u / SW;
        const size_t off = (size_t)(u + bh * (2 * FIN)) * TILE;
        if (!(n & 1)) sts32v(sb + SM_INFO + 4 * (n >> 1), ((n >> 1) << 16) | bh);
        mbar_expect_tx(sb + B_FULL + 8 * n, TILE);
        bulk_load(sb + n * TILE, ((n & 1) ? Vc : Kc) + off, TILE, sb + B_FULL + 8 * n, pol);
      }
      grab = atomicAdd(&g_grab[0], 1u);
      if (P_PREFETCH && owner) {
        bulk_prefetch((const char*)wg + cta * 11008, 11008);
        bulk_prefetch((const char*)wu + cta * 11008, 11008);
        bulk_prefetch((const char*)wd + cta * 11008, 11008);
        bulk_prefetch((const char*)wo + cta * 32768, 32768);
      }
#pragma unroll
      for (int n = DEPTH; n < 2 * NSTATIC; n++) {
        const unsigned u = cta + NCTA * (n >> 1), bh = u / SW;
        const size_t off = (size_t)(u + bh * (2 * FIN)) * TILE;
        mbar_wait(sb + B_FULL + 8 * (n - DEPTH), 0);
        if (!(n & 1)) sts32v(sb + SM_INFO + 4 * (n >> 1), ((n >> 1) << 16) | bh);
        mbar_expect_tx(sb + B_FULL + 8 * n, TILE);
        bulk_load(sb + n * TILE, ((n & 1) ? Vc : Kc) + off, TILE, sb + B_FULL + 8 * n, pol);
      }
    }
    __syncwarp();
    asm volatile("barrier.cluster.wait.acquire.aligned;" ::: "memory");
    if (lane == 0) {
      const unsigned base = lds32(sb + SM_EPOCH) * GRABS - (unsigned)(NSTATIC * NCTA);
      unsigned seq = NSTATIC, slot = NSTATIC % NSLOT, ph = (NSTATIC / NSLOT) ^ 1;
      unsigned ls = 2 * NSTATIC - DEPTH, lph = 0;
      int fin_left = owner ? FIN : 0;
      bool sweeping = true;
      unsigned wake = owner ? ((cta >> 1) + 1) * SW : 0xffffffffu, wake2 = 12 * SW;
      int infl = DEPTH, lim = DEPTH;
      while (true) {
        unsigned inf;
        size_t off;
        if (sweeping) {
          const unsigned u = grab - base;
          if (u >= wake) { mbar_arrive(sb + B_W); wake = 0xffffffffu; }
          if (u >= wake2) { mbar_arrive(sb + B_W2); wake2 = 0xffffffffu; }
          if (u < (unsigned)SWU) {
            grab = atomicAdd(&g_grab[0], 1u);
            const unsigned bh = u / SW;
            off = (size_t)(u + bh * (2 * FIN)) * TILE;
            inf = bh;
          } else {
            sweeping = false;
            lim = P_DF + (P_RK * (u - SWU)) / NCTA;
            TS(10);
          }
        }
        if (!sweeping) {
          if (fin_left == 0) break;
          fin_left--;
          off = (size_t)((cta >> 1) * UPH + SW + 2 * (FIN - 1 - fin_left) + (cta & 1)) * TILE;
          inf = (cta >> 1) | INF_FINAL;
        }
        mbar_wait(sb + B_EMPTY + 16 * slot, ph);
        sts32v(sb + SM_INFO + 4 * slot, (seq << 16) | inf);
        while (infl >= lim) {
          mbar_wait(sb + B_FULL + 8 * ls, lph);
          if (++ls == NST) { ls = 0; lph ^= 1; }
          infl--;
        }
        infl++;
        mbar_expect_tx(sb + B_FULL + 16 * slot, TILE);
        bulk_load(sb + (2 * slot) * TILE, Kc + off, TILE, sb + B_FULL + 16 * slot, pol);
        mbar_wait(sb + B_EMPTY + 16 * slot + 8, ph);
        while (infl >= lim) {
          mbar_wait(sb + B_FULL + 8 * ls, lph);
          if (++ls == NST) { ls = 0; lph ^= 1; }
          infl--;
        }
        infl++;
        mbar_expect_tx(sb + B_FULL + 16 * slot + 8, TILE);
        bulk_load(sb + (2 * slot + 1) * TILE, Vc + off, TILE, sb + B_FULL + 16 * slot + 8, pol);
        seq++;
        if (++slot == NSLOT) { slot = 0; ph ^= 1; }
      }
      if (!owner) {
        mbar_wait(sb + B_EMPTY + 16 * slot, ph);
        sts32v(sb + SM_INFO + 4 * slot, (seq << 16) | INF_END);
        mbar_arrive(sb + B_FULL + 16 * slot);
      }
    }
    return;
  }

  if (tid == 160) {
    unsigned epoch;
    asm volatile("ld.relaxed.gpu.global.u32 %0, [%1];" : "=r"(epoch) : "l"(&g_epoch[0]) : "memory");
    sts32(sb + SM_EPOCH, epoch);
  }
  __syncwarp();
  asm volatile("barrier.cluster.arrive.release.aligned;\nbarrier.cluster.wait.acquire.aligned;" ::: "memory");

  if (warp == 5) {
    const uint32_t tag = lds32(sb + SM_EPOCH) + 1u;
    const uint32_t par = tag & 1u;
    unsigned f = 0, ph = 0, nexth = 0;
    while (true) {
      mbar_wait(sb + B_FLF + 8 * f, ph);
      const uint32_t base = sb + SM_FL + f * (4 * 528);
      const uint4 meta = lds128(base + 512);
      float mj[4], lj[4];
      uint4 oj[4];
#pragma unroll
      for (int j = 0; j < 4; j++) {
        const float2 hh = lds64f(base + j * 528 + 512);
        mj[j] = hh.x; lj[j] = hh.y;
        oj[j] = lds128(base + j * 528 + lane * 16);
      }
      __syncwarp();
      if (lane == 0) mbar_arrive(sb + B_FLE + 8 * f);
      const float M = fmaxf(fmaxf(mj[0], mj[1]), fmaxf(mj[2], mj[3]));
      float o0 = 0.f, o1 = 0.f, o2 = 0.f, o3 = 0.f, L = 0.f;
#pragma unroll
      for (int j = 0; j < 4; j++) {
        const float e = ex2(mj[j] - M);
        L = fmaf(e, lj[j], L);
        o0 = fmaf(e, __uint_as_float(oj[j].x), o0); o1 = fmaf(e, __uint_as_float(oj[j].y), o1);
        o2 = fmaf(e, __uint_as_float(oj[j].z), o2); o3 = fmaf(e, __uint_as_float(oj[j].w), o3);
      }
      const unsigned bh = meta.z & 0xffu;
      const uint32_t b0 = __float_as_uint(o0);
      const uint32_t r0 = par ? ((b0 >> 16) | 1u) : (((b0 + 0x10000u) >> 16) & 0xfffeu);
      const uint32_t w0 = (pack_bf16(0.f, o1) & 0xffff0000u) | r0;
      st_relaxed64(g_part + (size_t)(bh * NCTA + cta) * 32 + lane, w0, pack_bf16(o2, o3));
      if (lane < 2) st_relaxed128(&g_hdr[(bh * NCTA + cta) * 2 + lane], __float_as_uint(M), tag, __float_as_uint(L), (tag << 8) | meta.w);
      const bool last = meta.z & 0x300u;
      for (; nexth < (last ? (unsigned)NBH : bh); nexth++)
        if (nexth != bh) st_relaxed64(g_part + (size_t)(nexth * NCTA + cta) * 32 + lane, par, 0u);
      nexth = bh + 1;
      if (last) break;
      if (++f == 2) { f = 0; ph ^= 1; }
    }
    if (lane == 0) TS(11);
    return;
  }

  {
    const int g = lane >> 2, t = lane & 3, mi = lane >> 3, ri = lane & 7;
    const uint32_t kofs = (warp * 16 + (mi & 1) * 8 + ri) * 256 + (mi >> 1) * 128;
    const uint32_t vofs = (warp * 16 + (mi >> 1) * 8 + ri) * 256 + (mi & 1) * 128 + TILE;
    const float sc = 0.08838834764831845f * 1.4426950408889634f;
    uint32_t q0[8], q1[8];
    float m = -INFINITY, l = 0.f;
    float o[2][4];
    unsigned cur = 0xffffu, nun = 0, seq = 0, slot = 0, ph = 0, f = 0, fph = 1;
    bool qall = false;
    const int cm = g ^ (2 * t);
    mbar_wait(sb + B_Q0, 0);
    while (true) {
      mbar_wait(sb + B_FULL + 16 * slot, ph);
      const unsigned inf = lds32v(sb + SM_INFO + 4 * slot) & 0xffffu;
      if (inf != cur) {
        if (inf & INF_END) break;
        cur = inf;
        const unsigned bh = inf & 0xffu;
        if (bh >= 2 && !qall) { mbar_wait(sb + B_Q1, 0); qall = true; }
#pragma unroll
        for (int c = 0; c < 8; c++) {
          q0[c] = lds32(sb + SM_Q + bh * 256 + ((c ^ g) << 4) + t * 4);
          q1[c] = lds32(sb + SM_Q + bh * 256 + 128 + ((c ^ g) << 4) + t * 4);
        }
        m = -INFINITY; l = 0.f; nun = 0;
#pragma unroll
        for (int i = 0; i < 4; i++) { o[0][i] = 0.f; o[1][i] = 0.f; }
      }
      const uint32_t st = sb + slot * (2 * TILE);
      float s[2][4];
#pragma unroll
      for (int i = 0; i < 4; i++) { s[0][i] = 0.f; s[1][i] = 0.f; }
#pragma unroll
      for (int c = 0; c < 8; c++) {
        uint32_t a0, a1, a2, a3;
        ldsm4(st + kofs + ((c ^ ri) << 4), a0, a1, a2, a3);
        mma16816(s[c & 1], a0, a1, a2, a3, q0[c], q1[c]);
      }
      const float s0 = __shfl_sync(~0u, s[0][0] + s[1][0], 9 * t);
      const float s1 = __shfl_sync(~0u, s[0][1] + s[1][1], 9 * t + 4);
      const float s2 = __shfl_sync(~0u, s[0][2] + s[1][2], 9 * t);
      const float s3 = __shfl_sync(~0u, s[0][3] + s[1][3], 9 * t + 4);
      if (lane == 0) mbar_arrive(sb + B_EMPTY + 16 * slot);
      float mx = fmaxf(fmaxf(s0, s1), fmaxf(s2, s3));
      mx = fmaxf(mx, __shfl_xor_sync(~0u, mx, 1));
      mx = fmaxf(mx, __shfl_xor_sync(~0u, mx, 2));
      const float mn = fmaxf(m, mx * sc);
      const float alpha = ex2(m - mn);
      m = mn;
      const float p0 = ex2(fmaf(s0, sc, -mn)), p1 = ex2(fmaf(s1, sc, -mn));
      const float p2 = ex2(fmaf(s2, sc, -mn)), p3 = ex2(fmaf(s3, sc, -mn));
      l = fmaf(l, alpha, (p0 + p1) + (p2 + p3));
      const uint32_t pb0 = pack_bf16(p0, p1), pb1 = pack_bf16(p2, p3);
#pragma unroll
      for (int i = 0; i < 4; i++) { o[0][i] *= alpha; o[1][i] *= alpha; }
      mbar_wait(sb + B_FULL + 16 * slot + 8, ph);
#pragma unroll
      for (int c = 0; c < 8; c++) {
        uint32_t a0, a1, a2, a3;
        ldsm4t(st + vofs + ((c ^ ri) << 4), a0, a1, a2, a3);
        const uint32_t msk = (c == cm) ? 0x0000ffffu : ((c == (cm ^ 1)) ? 0xffff0000u : 0u);
        mma16816(o[c & 1], a0, a1, a2, a3, pb0 & msk, pb1 & msk);
      }
      nun++;
      seq++;
      if (cur & INF_FINAL) {
        if (nun == FIN) break;
        __syncwarp();
        if (lane == 0) mbar_arrive(sb + B_EMPTY + 16 * slot + 8);
        if (++slot == NSLOT) { slot = 0; ph ^= 1; }
        continue;
      }
      __syncwarp();
      if (lane == 0) mbar_arrive(sb + B_EMPTY + 16 * slot + 8);
      if (++slot == NSLOT) { slot = 0; ph ^= 1; }
      unsigned nx = lds32v(sb + SM_INFO + 4 * slot);
      if ((nx >> 16) != (seq & 0xffffu)) {
        mbar_wait(sb + B_FULL + 16 * slot, ph);
        nx = lds32v(sb + SM_INFO + 4 * slot);
      }
      nx &= 0xffffu;
      if (nx != cur) {
        float lr = l + __shfl_xor_sync(~0u, l, 1);
        lr += __shfl_xor_sync(~0u, lr, 2);
        mbar_wait(sb + B_FLE + 8 * f, fph);
        const uint32_t base = sb + SM_FL + f * (4 * 528) + warp * 528;
        sts128(base + lane * 16, __float_as_uint(o[0][0] + o[1][0]), __float_as_uint(o[0][1] + o[1][1]),
               __float_as_uint(o[0][2] + o[1][2]), __float_as_uint(o[0][3] + o[1][3]));
        if (lane == 0) sts128(base + 512, __float_as_uint(m), __float_as_uint(lr), cur | (nx & 0x300u), nun);
        __syncwarp();
        if (lane == 0) mbar_arrive(sb + B_FLF + 8 * f);
        if (++f == 2) { f = 0; fph ^= 1; }
      }
    }
    if (owner) {
      float lr = l + __shfl_xor_sync(~0u, l, 1);
      lr += __shfl_xor_sync(~0u, lr, 2);
      const uint32_t v0 = pack_bf16(o[0][0] + o[1][0], o[0][1] + o[1][1]), v1 = pack_bf16(o[0][2] + o[1][2], o[0][3] + o[1][3]);
      const uint32_t dst = sb + SM_XS + ((cta & 1) * 4 + warp) * 272;
#pragma unroll
      for (int rk = 0; rk < 2; rk++) {
        const uint32_t rr = (cta & 1) ^ (rk ^ 1);
        const uint32_t d = mapa(dst, rr), bx = mapa(sb + B_X, rr);
        st_async64(d + lane * 8, v0, v1, bx);
        if (lane == 0) st_async64(d + 256, __float_as_uint(m), __float_as_uint(lr), bx);
      }
      if (tid == 0) TS(12);
    }
  }
}

}

extern "C" void kernel_launch(void* const* d_in, const int* in_sizes, int n_in, void* d_out, int out_size) {
  (void)in_sizes; (void)n_in; (void)out_size;
  static bool configured = false;
  if (!configured) {
    cudaFuncSetAttribute(fused_decode_kernel, cudaFuncAttributeMaxDynamicSharedMemorySize, SM_TOTAL);
    configured = true;
  }
  fused_decode_kernel<<<NCTA, NTHR, SM_TOTAL, cudaStreamPerThread>>>(
      (const __nv_bfloat16*)d_in[0], (const char*)d_in[1], (const char*)d_in[2], (const __nv_bfloat16*)d_in[3],
      (const __nv_bfloat16*)d_in[4], (const __nv_bfloat16*)d_in[6], (const __nv_bfloat16*)d_in[7],
      (const __nv_bfloat16*)d_in[8], (const __nv_bfloat16*)d_in[9], (__nv_bfloat16*)d_out);
}
```

```cpp
#include <cuda_runtime.h>
#include <cuda_bf16.h>
#include <stdint.h>

#define P_NST 10
#define P_D 3
#define P_DF 2
#define P_RK 0
#define P_YCLR 1
#define P_SPEC 62
#define P_QCLR 1
#define P_L0 2
#define P_DRY 3
#define P_FIN 4

namespace {

constexpr int NCTA = 132;
constexpr int NST = P_NST;
constexpr int FIN = P_FIN;
constexpr int UPH = 256;
constexpr int SW = UPH - 2 * FIN;
constexpr int NBH = 64;
constexpr int SWU = NBH * SW;
constexpr int DEPTH = P_D;
constexpr int NSLOT = NST / 2;
constexpr int NSTATIC = 2;
constexpr unsigned GRABS = SWU - NSTATIC * NCTA + NCTA;
constexpr int TILE = 16384;
constexpr int NTHR = 448;
constexpr int NGLU = 43;
constexpr int GLU0 = NCTA - NGLU;
constexpr int DF = 1376;

constexpr int SM_Q = NST * TILE;
constexpr int SM_FL = SM_Q + 16384;
constexpr int SM_XS = SM_FL + 2 * 4 * 528;
constexpr int SM_XS2 = SM_XS + 8 * 272;
constexpr int SM_RED = SM_XS2 + 8 * 272;
constexpr int SM_H = SM_RED + 4096;
constexpr int SM_G = SM_H + 256;
constexpr int SM_BAR = SM_G + 64;
constexpr int B_FULL = SM_BAR;
constexpr int B_EMPTY = B_FULL + 8 * NST;
constexpr int B_FLF = B_EMPTY + 8 * NST;
constexpr int B_FLE = B_FLF + 16;
constexpr int B_Q0 = B_FLE + 16;
constexpr int B_Q1 = B_Q0 + 8;
constexpr int B_X = B_Q1 + 8;
constexpr int B_W = B_X + 8;
constexpr int B_W2 = B_W + 8;
constexpr int SM_INFO = B_W2 + 8;
constexpr int SM_EPOCH = SM_INFO + 4 * 8;
constexpr int SM_TOTAL0 = SM_EPOCH + 16;
constexpr int SM_TOTAL = SM_TOTAL0 < 118 * 1024 ? 118 * 1024 : SM_TOTAL0;

constexpr float M_NONE = -3.0e38f;
constexpr unsigned INF_FINAL = 0x100u;
constexpr unsigned INF_END = 0x200u;

struct __align__(128) Scratch {
  unsigned epoch[1];
  unsigned grab[31];
  unsigned long long qbuf[4096];
  uint2 part[NBH * NCTA * 32];
  uint4 hdr[NBH * NCTA * 2];
  unsigned long long gbuf[NGLU * 1024];
  unsigned long long ybuf[32 * 1024];
};
__device__ Scratch g_scratch;
#define TS(i) do {} while (0)

#define T3X(i) i
constexpr long long SPIN_LIMIT = 2000000000ll;

__device__ __forceinline__ void mbar_init(uint32_t bar, uint32_t cnt) {
  asm volatile("mbarrier.init.shared::cta.b64 [%0], %1;" ::"r"(bar), "r"(cnt) : "memory");
}
__device__ __forceinline__ void mbar_expect_tx(uint32_t bar, uint32_t bytes) {
  asm volatile("mbarrier.arrive.expect_tx.shared::cta.b64 _, [%0], %1;" ::"r"(bar), "r"(bytes) : "memory");
}
__device__ __forceinline__ void mbar_arrive(uint32_t bar) {
  asm volatile("mbarrier.arrive.shared::cta.b64 _, [%0];" ::"r"(bar) : "memory");
}
__device__ __forceinline__ bool mbar_try(uint32_t bar, uint32_t parity) {
  uint32_t ok;
  asm volatile("{\n.reg .pred p;\nmbarrier.try_wait.parity.shared::cta.b64 p, [%1], %2;\nselp.u32 %0, 1, 0, p;\n}\n"
               : "=r"(ok) : "r"(bar), "r"(parity) : "memory");
  return ok != 0;
}
__device__ __forceinline__ void mbar_wait(uint32_t bar, uint32_t parity) {
  if (mbar_try(bar, parity)) return;
  long long t0 = clock64();
  while (!mbar_try(bar, parity)) {
    if (clock64() - t0 > SPIN_LIMIT) __trap();
  }
}
__device__ __forceinline__ void mbar_wait_n(uint32_t bar, uint32_t parity) {
  unsigned n = 0;
  while (!mbar_try(bar, parity))
    if (++n > (1u << 26)) __trap();
}
__device__ __forceinline__ unsigned grab_next(unsigned* ctr) {
  unsigned r;
  asm volatile("atom.relaxed.gpu.global.inc.u32 %0, [%1], %2;" : "=r"(r) : "l"(ctr), "n"(GRABS - 1) : "memory");
  return r;
}
__device__ __forceinline__ bool mbar_try_cluster(uint32_t bar, uint32_t parity) {
  uint32_t ok;
  asm volatile("{\n.reg .pred p;\nmbarrier.try_wait.parity.acquire.cluster.shared::cta.b64 p, [%1], %2;\nselp.u32 %0, 1, 0, p;\n}\n"
               : "=r"(ok) : "r"(bar), "r"(parity) : "memory");
  return ok != 0;
}
__device__ __forceinline__ void mbar_wait_cluster(uint32_t bar, uint32_t parity) {
  if (mbar_try_cluster(bar, parity)) return;
  long long t0 = clock64();
  while (!mbar_try_cluster(bar, parity)) {
    if (clock64() - t0 > SPIN_LIMIT) __trap();
  }
}
__device__ __forceinline__ void bulk_load(uint32_t dst, const void* src, uint32_t bytes, uint32_t bar, uint64_t pol) {
  asm volatile("cp.async.bulk.shared::cluster.global.mbarrier::complete_tx::bytes.L2::cache_hint [%0], [%1], %2, [%3], %4;"
               ::"r"(dst), "l"(src), "r"(bytes), "r"(bar), "l"(pol) : "memory");
}
__device__ __forceinline__ void ldsm4(uint32_t addr, uint32_t& a0, uint32_t& a1, uint32_t& a2, uint32_t& a3) {
  asm volatile("ldmatrix.sync.aligned.m8n8.x4.shared.b16 {%0,%1,%2,%3}, [%4];"
               : "=r"(a0), "=r"(a1), "=r"(a2), "=r"(a3) : "r"(addr) : "memory");
}
__device__ __forceinline__ void ldsm4t(uint32_t addr, uint32_t& a0, uint32_t& a1, uint32_t& a2, uint32_t& a3) {
  asm volatile("ldmatrix.sync.aligned.m8n8.x4.trans.shared.b16 {%0,%1,%2,%3}, [%4];"
               : "=r"(a0), "=r"(a1), "=r"(a2), "=r"(a3) : "r"(addr) : "memory");
}
__device__ __forceinline__ void mma16816(float (&c)[4], uint32_t a0, uint32_t a1, uint32_t a2, uint32_t a3, uint32_t b0, uint32_t b1) {
  asm volatile("mma.sync.aligned.m16n8k16.row.col.f32.bf16.bf16.f32 {%0,%1,%2,%3}, {%4,%5,%6,%7}, {%8,%9}, {%0,%1,%2,%3};"
               : "+f"(c[0]), "+f"(c[1]), "+f"(c[2]), "+f"(c[3]) : "r"(a0), "r"(a1), "r"(a2), "r"(a3), "r"(b0), "r"(b1));
}
__device__ __forceinline__ uint32_t lds32(uint32_t a) { uint32_t v; asm volatile("ld.shared.b32 %0, [%1];" : "=r"(v) : "r"(a) : "memory"); return v; }
__device__ __forceinline__ uint32_t lds32v(uint32_t a) { uint32_t v; asm volatile("ld.volatile.shared.b32 %0, [%1];" : "=r"(v) : "r"(a) : "memory"); return v; }
__device__ __forceinline__ float2 lds64f(uint32_t a) { float2 v; asm volatile("ld.shared.v2.f32 {%0,%1}, [%2];" : "=f"(v.x), "=f"(v.y) : "r"(a) : "memory"); return v; }
__device__ __forceinline__ uint4 lds128(uint32_t a) { uint4 v; asm volatile("ld.shared.v4.b32 {%0,%1,%2,%3}, [%4];" : "=r"(v.x), "=r"(v.y), "=r"(v.z), "=r"(v.w) : "r"(a) : "memory"); return v; }
__device__ __forceinline__ void sts32(uint32_t a, uint32_t v) { asm volatile("st.shared.b32 [%0], %1;" ::"r"(a), "r"(v) : "memory"); }
__device__ __forceinline__ void sts32v(uint32_t a, uint32_t v) { asm volatile("st.volatile.shared.b32 [%0], %1;" ::"r"(a), "r"(v) : "memory"); }
__device__ __forceinline__ void sts64(uint32_t a, uint32_t x, uint32_t y) { asm volatile("st.shared.v2.b32 [%0], {%1,%2};" ::"r"(a), "r"(x), "r"(y) : "memory"); }
__device__ __forceinline__ void sts128(uint32_t a, uint32_t x, uint32_t y, uint32_t z, uint32_t w) { asm volatile("st.shared.v4.b32 [%0], {%1,%2,%3,%4};" ::"r"(a), "r"(x), "r"(y), "r"(z), "r"(w) : "memory"); }
__device__ __forceinline__ uint32_t pack_bf16(float lo, float hi) {
  uint32_t r; asm("cvt.rn.bf16x2.f32 %0, %1, %2;" : "=r"(r) : "f"(hi), "f"(lo)); return r;
}
__device__ __forceinline__ float bf_lo(uint32_t v) { return __uint_as_float(v << 16); }
__device__ __forceinline__ float bf_hi(uint32_t v) { return __uint_as_float(v & 0xffff0000u); }
__device__ __forceinline__ float bf_round(float v) { return __bfloat162float(__float2bfloat16_rn(v)); }
__device__ __forceinline__ float ex2(float v) { float r; asm("ex2.approx.ftz.f32 %0, %1;" : "=f"(r) : "f"(v)); return r; }
__device__ __forceinline__ void aux_bar() { asm volatile("bar.sync 1, 256;" ::: "memory"); }
__device__ __forceinline__ uint4 ldg128(const void* p) {
  uint4 v; asm volatile("ld.global.nc.v4.b32 {%0,%1,%2,%3}, [%4];" : "=r"(v.x), "=r"(v.y), "=r"(v.z), "=r"(v.w) : "l"(p)); return v;
}
__device__ __forceinline__ uint2 ldg64(const void* p) {
  uint2 v; asm volatile("ld.global.nc.v2.b32 {%0,%1}, [%2];" : "=r"(v.x), "=r"(v.y) : "l"(p)); return v;
}
__device__ __forceinline__ uint4 ld_relaxed128(const void* p) {
  unsigned long long a, b;
  asm volatile("ld.relaxed.gpu.global.v2.b64 {%0,%1}, [%2];" : "=l"(a), "=l"(b) : "l"(p) : "memory");
  return make_uint4((uint32_t)a, (uint32_t)(a >> 32), (uint32_t)b, (uint32_t)(b >> 32));
}
__device__ __forceinline__ uint2 ld_relaxed64(const void* p) {
  unsigned long long a;
  asm volatile("ld.relaxed.gpu.global.b64 %0, [%1];" : "=l"(a) : "l"(p) : "memory");
  return make_uint2((uint32_t)a, (uint32_t)(a >> 32));
}
__device__ __forceinline__ void st_relaxed64(void* p, uint32_t lo, uint32_t hi) {
  unsigned long long a = ((unsigned long long)hi << 32) | lo;
  asm volatile("st.relaxed.gpu.global.b64 [%0], %1;" ::"l"(p), "l"(a) : "memory");
}
__device__ __forceinline__ void st_relaxed128(void* p, uint32_t lo0, uint32_t hi0, uint32_t lo1, uint32_t hi1) {
  unsigned long long a = ((unsigned long long)hi0 << 32) | lo0, b = ((unsigned long long)hi1 << 32) | lo1;
  asm volatile("st.relaxed.gpu.global.v2.b64 [%0], {%1,%2};" ::"l"(p), "l"(a), "l"(b) : "memory");
}
__device__ __forceinline__ uint4 ldcg128(const void* p) {
  uint4 v; asm volatile("ld.global.cg.v4.b32 {%0,%1,%2,%3}, [%4];" : "=r"(v.x), "=r"(v.y), "=r"(v.z), "=r"(v.w) : "l"(p) : "memory"); return v;
}
__device__ __forceinline__ void st_async64(uint32_t addr, uint32_t x, uint32_t y, uint32_t bar) {
  asm volatile("st.async.shared::cluster.mbarrier::complete_tx::bytes.v2.b32 [%0], {%1,%2}, [%3];" ::"r"(addr), "r"(x), "r"(y), "r"(bar) : "memory");
}
__device__ __forceinline__ uint32_t mapa(uint32_t addr, uint32_t rank) {
  uint32_t r; asm("mapa.shared::cluster.u32 %0, %1, %2;" : "=r"(r) : "r"(addr), "r"(rank)); return r;
}

__device__ __forceinline__ void gemv32_reduce(const uint4 (&w)[8], const uint4& x0, const uint4& x1, uint32_t red, int warp, int lane) {
  float a0[8], a1[8];
#pragma unroll
  for (int j = 0; j < 8; j++) { a0[j] = 0.f; a1[j] = 0.f; }
  const uint32_t xa[4] = {x0.x, x0.y, x0.z, x0.w}, xb[4] = {x1.x, x1.y, x1.z, x1.w};
#pragma unroll
  for (int j = 0; j < 8; j++) {
    const float fa = (j & 1) ? bf_hi(xa[j >> 1]) : bf_lo(xa[j >> 1]);
    const float fb = (j & 1) ? bf_hi(xb[j >> 1]) : bf_lo(xb[j >> 1]);
    const uint32_t ww[4] = {w[j].x, w[j].y, w[j].z, w[j].w};
#pragma unroll
    for (int i = 0; i < 4; i++) {
      const float lo = bf_lo(ww[i]), hi = bf_hi(ww[i]);
      a0[2 * i] = fmaf(fa, lo, a0[2 * i]); a0[2 * i + 1] = fmaf(fa, hi, a0[2 * i + 1]);
      a1[2 * i] = fmaf(fb, lo, a1[2 * i]); a1[2 * i + 1] = fmaf(fb, hi, a1[2 * i + 1]);
    }
  }
  const bool b4 = lane & 16, b3 = lane & 8, b2 = lane & 4;
  float v[8];
#pragma unroll
  for (int j = 0; j < 8; j++) v[j] = (b4 ? a1[j] : a0[j]) + __shfl_xor_sync(~0u, b4 ? a0[j] : a1[j], 16);
  float u[4];
#pragma unroll
  for (int j = 0; j < 4; j++) u[j] = (b3 ? v[j + 4] : v[j]) + __shfl_xor_sync(~0u, b3 ? v[j] : v[j + 4], 8);
  const float r0 = (b2 ? u[2] : u[0]) + __shfl_xor_sync(~0u, b2 ? u[0] : u[2], 4);
  const float r1 = (b2 ? u[3] : u[1]) + __shfl_xor_sync(~0u, b2 ? u[1] : u[3], 4);
  const int idx = (b4 ? 32 : 0) + (lane & 3) * 8 + (b3 ? 4 : 0) + (b2 ? 2 : 0);
  sts64(red + (warp * 64 + idx) * 4, __float_as_uint(r0), __float_as_uint(r1));
}
__device__ __forceinline__ float2 gemv32_final(uint32_t red, int i  ) {
  float2 s = make_float2(0.f, 0.f);
#pragma unroll
  for (int w = 0; w < 8; w++) { float2 v = lds64f(red + (w * 64 + 2 * i) * 4); s.x += v.x; s.y += v.y; }
  return s;
}

__device__ __forceinline__ void wo_mma(const uint32_t (&A)[8][8], uint32_t slot, int g, int t, float (&c)[4][4]) {
  uint4 bv[4];
#pragma unroll
  for (int j = 0; j < 4; j++) bv[j] = lds128(slot + g * 272 + t * 64 + ((j ^ ((t >> 1) << 1)) << 4));
#pragma unroll
  for (int i = 0; i < 4; i++) { c[i][0] = 0.f; c[i][1] = 0.f; c[i][2] = 0.f; c[i][3] = 0.f; }
#pragma unroll
  for (int j = 0; j < 4; j++) {
    mma16816(c[0], A[2 * j][0], A[2 * j][1], A[2 * j][2], A[2 * j][3], bv[j].x, bv[j].y);
    mma16816(c[1], A[2 * j][4], A[2 * j][5], A[2 * j][6], A[2 * j][7], bv[j].x, bv[j].y);
    mma16816(c[2], A[2 * j + 1][0], A[2 * j + 1][1], A[2 * j + 1][2], A[2 * j + 1][3], bv[j].z, bv[j].w);
    mma16816(c[3], A[2 * j + 1][4], A[2 * j + 1][5], A[2 * j + 1][6], A[2 * j + 1][7], bv[j].z, bv[j].w);
  }
}
__device__ __forceinline__ float wo_reduce(const float (&c)[4][4], float w0, float w1, int t) {
  const float y0 = w0 * (c[0][0] + c[2][0]) + w1 * (c[0][1] + c[2][1]);
  const float y1 = w0 * (c[0][2] + c[2][2]) + w1 * (c[0][3] + c[2][3]);
  const float y2 = w0 * (c[1][0] + c[3][0]) + w1 * (c[1][1] + c[3][1]);
  const float y3 = w0 * (c[1][2] + c[3][2]) + w1 * (c[1][3] + c[3][3]);
  const bool b1 = t & 2, b0 = t & 1;
  const float z0 = (b1 ? y2 : y0) + __shfl_xor_sync(~0u, b1 ? y0 : y2, 2);
  const float z1 = (b1 ? y3 : y1) + __shfl_xor_sync(~0u, b1 ? y1 : y3, 2);
  return (b0 ? z1 : z0) + __shfl_xor_sync(~0u, b0 ? z0 : z1, 1);
}

__global__ void __cluster_dims__(2, 1, 1) __launch_bounds__(NTHR, 1)
fused_decode_kernel(const char* __restrict__ Kc, const char* __restrict__ Vc, Scratch* sc_,
                    const __nv_bfloat16* __restrict__ x, const __nv_bfloat16* __restrict__ wq,
                    const __nv_bfloat16* __restrict__ wo,
                    const __nv_bfloat16* __restrict__ wg, const __nv_bfloat16* __restrict__ wu,
                    const __nv_bfloat16* __restrict__ wd, const __nv_bfloat16* __restrict__ gw,
                    __nv_bfloat16* __restrict__ out) {
  extern __shared__ __align__(1024) unsigned char smem_raw[];
  const uint32_t sb = (uint32_t)__cvta_generic_to_shared(smem_raw);
  const int tid = threadIdx.x, warp = tid >> 5, lane = tid & 31;
  const int cta = blockIdx.x;
  const bool owner = cta < 128;
  uint64_t pol;
  asm volatile("createpolicy.fractional.L2::evict_first.b64 %0, 1.0;" : "=l"(pol));
  unsigned epoch = 0;
  if (warp == 1) asm volatile("ld.relaxed.gpu.global.u32 %0, [%1];" : "=r"(epoch) : "l"(&sc_->epoch[0]) : "memory");
  if (tid == 0) {
    mbar_init(sb + B_FULL, 1);
    mbar_init(sb + B_FULL + 8, 1);
    asm volatile("fence.proxy.async.shared::cta;" ::: "memory");
    mbar_expect_tx(sb + B_FULL, TILE);
    bulk_load(sb, Kc + (size_t)cta * TILE, TILE, sb + B_FULL, pol);
    mbar_expect_tx(sb + B_FULL + 8, TILE);
    bulk_load(sb + TILE, Vc + (size_t)cta * TILE, TILE, sb + B_FULL + 8, pol);
  }

  if (warp >= 6) {
    const int at = tid - 192, aw = warp - 6;
    const int g = lane >> 2, t = lane & 3;
    uint4 w[8];
    const int rg = at >> 2, cq = at & 3;
    asm volatile("barrier.cluster.arrive.relaxed.aligned;" ::: "memory");
#pragma unroll
    for (int j = 0; j < 8; j++) {
      w[j] = make_uint4(0, 0, 0, 0);
      if (owner) w[j] = ldg128(wq + (size_t)(rg * 8 + j) * 4096 + cta * 32 + cq * 8);
    }
    const uint4 x0 = ldg128(x + rg * 8), x1 = ldg128(x + 512 + rg * 8);
    if (owner || (P_DRY & 2)) gemv32_reduce(w, x0, x1, sb + SM_RED, aw, lane);
    asm volatile("barrier.cluster.wait.acquire.aligned;" ::: "memory");
    const uint32_t tag = lds32(sb + SM_EPOCH) + 1u;
    aux_bar();
    if (at < 32) {
      const float2 s = gemv32_final(sb + SM_RED, at);
      if (owner) st_relaxed64(&sc_->qbuf[(at >> 4) * 2048 + cta * 16 + (at & 15)], pack_bf16(s.x, s.y), tag);
    }
    if (at == 0) TS(1);
    if (at < 64) {
      long long t0 = clock64();
      uint4 v = ld_relaxed128(&sc_->qbuf[at * 2]);
      while (v.y != tag || v.w != tag) {
        if (clock64() - t0 > SPIN_LIMIT) __trap();
        v = ld_relaxed128(&sc_->qbuf[at * 2]);
      }
      sts64(sb + SM_Q + at * 8, v.x, v.z);
      __syncwarp();
      if (lane == 0) mbar_arrive(sb + B_Q0);
    }
    if (at == 0) TS(2);
    aux_bar();
    {
      uint4 v[8];
#pragma unroll
      for (int j = 0; j < 8; j++) v[j] = ld_relaxed128(&sc_->qbuf[(j * 256 + at) * 2]);
      long long t0 = clock64();
#pragma unroll
      for (int j = 0; j < 8; j++) {
        while (v[j].y != tag || v[j].w != tag) {
          if (clock64() - t0 > SPIN_LIMIT) __trap();
          v[j] = ld_relaxed128(&sc_->qbuf[(j * 256 + at) * 2]);
        }
        if (j > 0 || at >= 64) sts64(sb + SM_Q + (j * 256 + at) * 8, v[j].x, v[j].z);
      }
      __syncwarp();
      if (lane == 0) mbar_arrive(sb + B_Q1);
    }
    if (at == 0) TS(3);
    if (cta >= GLU0) {
      const int f = cta - GLU0;
      uint4 w2[8];
#pragma unroll
      for (int j = 0; j < 8; j++) w[j] = ldg128(wg + (size_t)(rg * 8 + j) * DF + f * 32 + cq * 8);
#pragma unroll
      for (int j = 0; j < 8; j++) w2[j] = ldg128(wu + (size_t)(rg * 8 + j) * DF + f * 32 + cq * 8);
      gemv32_reduce(w, x0, x1, sb + SM_RED, aw, lane);
      const int dr = lane >> 3, dc = aw * 64 + (lane & 7) * 8;
#pragma unroll
      for (int j = 0; j < 8; j++) w[j] = ldg128(wd + (size_t)(f * 32 + dr * 8 + j) * 512 + dc);
      gemv32_reduce(w2, x0, x1, sb + SM_RED + 2048, aw, lane);
      aux_bar();
      if (at < 32) {
        const float2 gs = gemv32_final(sb + SM_RED, at), us = gemv32_final(sb + SM_RED + 2048, at);
        float hh[2];
#pragma unroll
        for (int i = 0; i < 2; i++) {
          const float gv = bf_round(i ? gs.y : gs.x), uv = bf_round(i ? us.y : us.x);
          const float inner = 0.7978845608028654f * (gv + 0.044715f * gv * gv * gv);
          const float ge = bf_round(0.5f * gv * (1.f + tanhf(inner)));
          hh[i] = bf_round(ge * uv);
        }
        sts64(sb + SM_H + at * 8, __float_as_uint(hh[0]), __float_as_uint(hh[1]));
      }
      aux_bar();
      float a0[8], a1[8];
#pragma unroll
      for (int j = 0; j < 8; j++) { a0[j] = 0.f; a1[j] = 0.f; }
#pragma unroll
      for (int j = 0; j < 8; j++) {
        const float fa = __uint_as_float(lds32(sb + SM_H + (dr * 8 + j) * 4));
        const float fb = __uint_as_float(lds32(sb + SM_H + (32 + dr * 8 + j) * 4));
        const uint32_t ww[4] = {w[j].x, w[j].y, w[j].z, w[j].w};
#pragma unroll
        for (int i = 0; i < 4; i++) {
          const float lo = bf_lo(ww[i]), hi = bf_hi(ww[i]);
          a0[2 * i] = fmaf(fa, lo, a0[2 * i]); a0[2 * i + 1] = fmaf(fa, hi, a0[2 * i + 1]);
          a1[2 * i] = fmaf(fb, lo, a1[2 * i]); a1[2 * i + 1] = fmaf(fb, hi, a1[2 * i + 1]);
        }
      }
      const bool b4 = lane & 16, b3 = lane & 8;
      float v[8], u[4];
#pragma unroll
      for (int j = 0; j < 8; j++) v[j] = (b4 ? a1[j] : a0[j]) + __shfl_xor_sync(~0u, b4 ? a0[j] : a1[j], 16);
#pragma unroll
      for (int j = 0; j < 4; j++) u[j] = (b3 ? v[j + 4] : v[j]) + __shfl_xor_sync(~0u, b3 ? v[j] : v[j + 4], 8);
      unsigned long long* dst = &sc_->gbuf[f * 1024 + (b4 ? 512 : 0) + dc + (b3 ? 4 : 0)];
      st_relaxed128(dst, __float_as_uint(u[0]), tag, __float_as_uint(u[1]), tag);
      st_relaxed128(dst + 2, __float_as_uint(u[2]), tag, __float_as_uint(u[3]), tag);
    }
    if (!owner) return;
    const int bh = cta >> 1, r = cta & 1, h = bh & 31, b = bh >> 5;
    const int n0 = 256 * r + 32 * aw;
    uint32_t A[8][8];
#pragma unroll
    for (int ks = 0; ks < 8; ks++) {
      const int L = 8 * t + (ks ^ ((t >> 1) << 2));
      const int d0 = 16 * (L & 3) + (L >> 2);
      const __nv_bfloat16* p = wo + (size_t)(h * 128 + d0) * 512 + n0 + 4 * g;
      const uint2 v0 = ldg64(p), v1 = ldg64(p + 8 * 512), v2 = ldg64(p + 64 * 512), v3 = ldg64(p + 72 * 512);
      A[ks][0] = __byte_perm(v0.x, v1.x, 0x5410); A[ks][1] = __byte_perm(v0.x, v1.x, 0x7632);
      A[ks][2] = __byte_perm(v2.x, v3.x, 0x5410); A[ks][3] = __byte_perm(v2.x, v3.x, 0x7632);
      A[ks][4] = __byte_perm(v0.y, v1.y, 0x5410); A[ks][5] = __byte_perm(v0.y, v1.y, 0x7632);
      A[ks][6] = __byte_perm(v2.y, v3.y, 0x5410); A[ks][7] = __byte_perm(v2.y, v3.y, 0x7632);
    }
    const int oi = cta * 8 + aw;
    {
      const int ob = oi >> 9;
      float s = 0.f;
#pragma unroll
      for (int j = 0; j < 2; j++) {
        const uint4 xv = ldg128(x + ob * 512 + j * 256 + lane * 8), gv = ldg128(gw + j * 256 + lane * 8);
        const uint32_t xx[4] = {xv.x, xv.y, xv.z, xv.w}, gg[4] = {gv.x, gv.y, gv.z, gv.w};
#pragma unroll
        for (int i = 0; i < 4; i++) s += bf_round(bf_lo(xx[i]) * bf_lo(gg[i])) + bf_round(bf_hi(xx[i]) * bf_hi(gg[i]));
      }
      if (P_YCLR) st_relaxed64(&sc_->ybuf[h * 1024 + b * 512 + n0 + lane], 0u, tag - 1u);
      mbar_wait(sb + B_W2, 0);
      float bs = 0.f;
      long long t0 = clock64();
#pragma unroll
      for (int j = 0; j < 2; j++) {
        const int f = j * 32 + lane;
        if (f < NGLU) {
          uint2 v = ld_relaxed64(&sc_->gbuf[f * 1024 + oi]);
          while (v.y != tag) {
            if (clock64() - t0 > SPIN_LIMIT) __trap();
            __nanosleep(200);
            v = ld_relaxed64(&sc_->gbuf[f * 1024 + oi]);
          }
          bs += __uint_as_float(v.x);
        }
      }
#pragma unroll
      for (int o = 16; o > 0; o >>= 1) { s += __shfl_xor_sync(~0u, s, o); bs += __shfl_xor_sync(~0u, bs, o); }
      s = bf_round(s);
      const float gate = bf_round(1.f / (1.f + expf(-s)));
      const float gluterm = bf_round(bf_round(1.f - gate) * bf_round(bs));
      if (lane == 0) sts64(sb + SM_G + aw * 8, __float_as_uint(gate), __float_as_uint(gluterm));
    }
    if (at == 0) TS(4);
    mbar_wait(sb + B_W, 0);
    {
      const int pg = at >> 4, c16 = at & 15;
      const int hi = (lane >> 1) * 16 + 2 * aw + (lane & 1);
      uint4 hd, pv[9];
      const uint2* part = sc_->part + (size_t)bh * (NCTA * 32);
      const uint32_t par = tag & 1u;
      bool ldd = bh >= P_SPEC;
      long long t0 = clock64();
      while (true) {
        hd = make_uint4(__float_as_uint(M_NONE), tag, 0u, tag);
        if (hi < NCTA) hd = ld_relaxed128(&sc_->hdr[(bh * NCTA + hi) * 2]);
        uint32_t bad = ldd ? 0u : 1u;
#pragma unroll
        for (int k = 0; k < 9; k++) {
          const int i = k * 16 + pg;
          pv[k] = make_uint4(par, 0, par, 0);
          if (i < NCTA && ldd) pv[k] = ld_relaxed128(part + i * 32 + c16 * 2);
        }
#pragma unroll
        for (int k = 0; k < 9; k++) bad |= (pv[k].x ^ par) | (pv[k].z ^ par);
        const bool hok = __all_sync(~0u, hd.y == tag && hd.w == tag);
        if (hok && !__any_sync(~0u, bad & 1u)) break;
        if (hok) ldd = true;
        if (clock64() - t0 > SPIN_LIMIT) __trap();
      }
      float m = __uint_as_float(hd.x);
#pragma unroll
      for (int o = 16; o > 0; o >>= 1) m = fmaxf(m, __shfl_xor_sync(~0u, m, o));
      const float e = ex2(__uint_as_float(hd.x) - m);
      float l = e * __uint_as_float(hd.z);
#pragma unroll
      for (int o = 16; o > 0; o >>= 1) l += __shfl_xor_sync(~0u, l, o);
      float acc[8];
#pragma unroll
      for (int j = 0; j < 8; j++) acc[j] = 0.f;
#pragma unroll
      for (int k = 0; k < 9; k++) {
        const float wk = __shfl_sync(~0u, e, 2 * k + (lane >> 4));
        const uint32_t pp[4] = {pv[k].x, pv[k].y, pv[k].z, pv[k].w};
#pragma unroll
        for (int i = 0; i < 4; i++) {
          acc[2 * i] = fmaf(wk, bf_lo(pp[i]), acc[2 * i]);
          acc[2 * i + 1] = fmaf(wk, bf_hi(pp[i]), acc[2 * i + 1]);
        }
      }
#pragma unroll
      for (int j = 0; j < 8; j++) acc[j] += __shfl_xor_sync(~0u, acc[j], 16);
      if (lane < 16)
        sts128(sb + SM_XS2 + aw * 272 + c16 * 16, pack_bf16(acc[0], acc[1]), pack_bf16(acc[2], acc[3]),
               pack_bf16(acc[4], acc[5]), pack_bf16(acc[6], acc[7]));
      if (lane == 0) sts64(sb + SM_XS2 + aw * 272 + 256, __float_as_uint(m), __float_as_uint(l));
      aux_bar();
      if (at == 0) { TS(T3X(5)); if (cta == 0) asm volatile("st.relaxed.gpu.global.u32 [%0], %1;" ::"l"(&sc_->epoch[0]), "r"(tag) : "memory"); }
    }
    float Ms = M_NONE, Ls = 0.f, ys = 0.f;
    uint32_t xs = sb + SM_XS2;
    const float2 gg = lds64f(sb + SM_G + aw * 8);
#pragma unroll 1
    while (true) {
      const float2 h0 = lds64f(xs + (2 * t) * 272 + 256), h1 = lds64f(xs + (2 * t + 1) * 272 + 256);
      float c[4][4];
      wo_mma(A, xs, g, t, c);
      float M = fmaxf(fmaxf(h0.x, h1.x), Ms);
      M = fmaxf(M, __shfl_xor_sync(~0u, M, 1));
      M = fmaxf(M, __shfl_xor_sync(~0u, M, 2));
      const float e0 = ex2(h0.x - M), e1 = ex2(h1.x - M), es = ex2(Ms - M);
      float L = e0 * h0.y + e1 * h1.y;
      L += __shfl_xor_sync(~0u, L, 1);
      L += __shfl_xor_sync(~0u, L, 2);
      Ls = fmaf(es, Ls, L);
      Ms = M;
      ys = fmaf(es, ys, wo_reduce(c, e0, e1, t));
      if (xs == sb + SM_XS) break;
      xs = sb + SM_XS;
      asm volatile("" : "+r"(xs));
      if (at == 0) TS(T3X(6));
      mbar_wait_cluster(sb + B_X, 0);
      if (at == 0) TS(T3X(7));
    }
    st_relaxed64(&sc_->ybuf[h * 1024 + b * 512 + n0 + lane], __float_as_uint(__fdividef(ys, Ls)), tag);
    if (at == 0) TS(8);
    {
      const unsigned long long* p = &sc_->ybuf[lane * 1024 + oi];
      uint2 v = ld_relaxed64(p);
      unsigned n = 0;
      while (v.y != tag) {
        if (++n > (1u << 22)) __trap();
        v = ld_relaxed64(p);
      }
      float a = __uint_as_float(v.x);
#pragma unroll
      for (int o = 16; o > 0; o >>= 1) a += __shfl_xor_sync(~0u, a, o);
      if (lane == 0) out[oi] = __float2bfloat16_rn(bf_round(gg.x * bf_round(a)) + gg.y);
    }
    if (at == 0) TS(9);
    return;
  }

  if (warp != 4) {
  if (warp == 5) {
    if (lane == 0) {
#pragma unroll
      for (int s = 2; s < NST; s++) mbar_init(sb + B_FULL + 8 * s, 1);
#pragma unroll
      for (int s = 0; s < NST; s++) mbar_init(sb + B_EMPTY + 8 * s, 4);
      mbar_init(sb + B_W, 1); mbar_init(sb + B_W2, 1);
      mbar_init(sb + B_FLF, 4); mbar_init(sb + B_FLF + 8, 4); mbar_init(sb + B_FLE, 1); mbar_init(sb + B_FLE + 8, 1);
      mbar_init(sb + B_Q0, 2); mbar_init(sb + B_Q1, 8); mbar_init(sb + B_X, 1);
      mbar_expect_tx(sb + B_X, 8 * (256 + 8));
#pragma unroll
      for (int n = 0; n < NSLOT; n++)
        sts32v(sb + SM_INFO + 4 * n, n == 0 ? 0u : 0xffffffffu);
      asm volatile("fence.mbarrier_init.release.cluster;" ::: "memory");
      asm volatile("fence.proxy.async.shared::cta;" ::: "memory");
    }
  } else if (warp == 1) {
    if (lane == 0) sts32(sb + SM_EPOCH, epoch);
    if (P_QCLR && owner) st_relaxed64(&sc_->qbuf[(lane >> 4) * 2048 + cta * 16 + (lane & 15)], 0u, epoch);
  }
  __syncwarp();
  if (warp == 0 || warp == 5) asm volatile("bar.arrive 2, 96;" ::: "memory");
  asm volatile("fence.acq_rel.cta;" ::: "memory");
  asm volatile("barrier.cluster.arrive.relaxed.aligned;\nbarrier.cluster.wait.acquire.aligned;" ::: "memory");

  if (warp == 5) {
    const uint32_t tag = lds32(sb + SM_EPOCH) + 1u;
    const uint32_t par = tag & 1u;
    unsigned f = 0, ph = 0, nexth = 0;
    while (true) {
      mbar_wait(sb + B_FLF + 8 * f, ph);
      const uint32_t base = sb + SM_FL + f * (4 * 528);
      const uint4 meta = lds128(base + 512);
      float mj[4], lj[4];
      uint4 oj[4];
#pragma unroll
      for (int j = 0; j < 4; j++) {
        const float2 hh = lds64f(base + j * 528 + 512);
        mj[j] = hh.x; lj[j] = hh.y;
        oj[j] = lds128(base + j * 528 + lane * 16);
      }
      __syncwarp();
      if (lane == 0) mbar_arrive(sb + B_FLE + 8 * f);
      const float M = fmaxf(fmaxf(mj[0], mj[1]), fmaxf(mj[2], mj[3]));
      float o0 = 0.f, o1 = 0.f, o2 = 0.f, o3 = 0.f, L = 0.f;
#pragma unroll
      for (int j = 0; j < 4; j++) {
        const float e = ex2(mj[j] - M);
        L = fmaf(e, lj[j], L);
        o0 = fmaf(e, __uint_as_float(oj[j].x), o0); o1 = fmaf(e, __uint_as_float(oj[j].y), o1);
        o2 = fmaf(e, __uint_as_float(oj[j].z), o2); o3 = fmaf(e, __uint_as_float(oj[j].w), o3);
      }
      const unsigned bh = meta.z & 0xffu;
      const uint32_t b0 = __float_as_uint(o0);
      const uint32_t r0 = par ? ((b0 >> 16) | 1u) : (((b0 + 0x10000u) >> 16) & 0xfffeu);
      const uint32_t w0 = (pack_bf16(0.f, o1) & 0xffff0000u) | r0;
      st_relaxed64(sc_->part + (size_t)(bh * NCTA + cta) * 32 + lane, w0, pack_bf16(o2, o3));
      if (lane < 2) st_relaxed128(&sc_->hdr[(bh * NCTA + cta) * 2 + lane], __float_as_uint(M), tag, __float_as_uint(L), tag);
      const bool last = meta.z & 0x300u;
      for (; nexth < (last ? (unsigned)NBH : bh); nexth++)
        if (nexth != bh) {
          st_relaxed64(sc_->part + (size_t)(nexth * NCTA + cta) * 32 + lane, par, 0u);
          if (lane < 2) st_relaxed128(&sc_->hdr[(nexth * NCTA + cta) * 2 + lane], __float_as_uint(M_NONE), tag, 0u, tag);
        }
      nexth = bh + 1;
      if (last) break;
      if (++f == 2) { f = 0; ph ^= 1; }
    }
    if (lane == 0) TS(11);
    return;
  }

  {
    const int g = lane >> 2, t = lane & 3, mi = lane >> 3, ri = lane & 7;
    const uint32_t kofs = (warp * 16 + (mi & 1) * 8 + ri) * 256 + (mi >> 1) * 128;
    const uint32_t vofs = (warp * 16 + (mi >> 1) * 8 + ri) * 256 + (mi & 1) * 128 + TILE;
    const float sc = 0.08838834764831845f * 1.4426950408889634f;
    uint32_t q0[8], q1[8];
    float m = -INFINITY, l = 0.f;
    float o[2][4];
    unsigned cur = 0xffffu, nun = 0, seq = 0, slot = 0, ph = 0, f = 0, fph = 1;
    bool qall = false;
    const int cm = g ^ (2 * t);
    bool dry = P_DRY & 1;
    if (!dry) mbar_wait(sb + B_Q0, 0);
    while (true) {
      if (!dry) mbar_wait(sb + B_FULL + 16 * slot, ph);
      const unsigned inf = lds32v(sb + SM_INFO + 4 * slot) & 0xffffu;
      if (inf != cur) {
        if (inf & INF_END) break;
        cur = inf;
        const unsigned bh = inf & 0xffu;
        if (bh >= 2 && !qall) { mbar_wait(sb + B_Q1, 0); qall = true; }
#pragma unroll
        for (int c = 0; c < 8; c++) {
          q0[c] = lds32(sb + SM_Q + bh * 256 + ((c ^ g) << 4) + t * 4);
          q1[c] = lds32(sb + SM_Q + bh * 256 + 128 + ((c ^ g) << 4) + t * 4);
        }
        m = -INFINITY; l = 0.f; nun = 0;
#pragma unroll
        for (int i = 0; i < 4; i++) { o[0][i] = 0.f; o[1][i] = 0.f; }
      }
      const uint32_t st = sb + slot * (2 * TILE);
      float s[2][4];
#pragma unroll
      for (int i = 0; i < 4; i++) { s[0][i] = 0.f; s[1][i] = 0.f; }
#pragma unroll
      for (int c = 0; c < 8; c++) {
        uint32_t a0, a1, a2, a3;
        ldsm4(st + kofs + ((c ^ ri) << 4), a0, a1, a2, a3);
        mma16816(s[c & 1], a0, a1, a2, a3, q0[c], q1[c]);
      }
      const float s0 = __shfl_sync(~0u, s[0][0] + s[1][0], 9 * t);
      const float s1 = __shfl_sync(~0u, s[0][1] + s[1][1], 9 * t + 4);
      const float s2 = __shfl_sync(~0u, s[0][2] + s[1][2], 9 * t);
      const float s3 = __shfl_sync(~0u, s[0][3] + s[1][3], 9 * t + 4);
      if (lane == 0 && !dry) mbar_arrive(sb + B_EMPTY + 16 * slot);
      float mx = fmaxf(fmaxf(s0, s1), fmaxf(s2, s3));
      mx = fmaxf(mx, __shfl_xor_sync(~0u, mx, 1));
      mx = fmaxf(mx, __shfl_xor_sync(~0u, mx, 2));
      const float mn = fmaxf(m, mx * sc);
      const float alpha = ex2(m - mn);
      m = mn;
      const float p0 = ex2(fmaf(s0, sc, -mn)), p1 = ex2(fmaf(s1, sc, -mn));
      const float p2 = ex2(fmaf(s2, sc, -mn)), p3 = ex2(fmaf(s3, sc, -mn));
      l = fmaf(l, alpha, (p0 + p1) + (p2 + p3));
      const uint32_t pb0 = pack_bf16(p0, p1), pb1 = pack_bf16(p2, p3);
#pragma unroll
      for (int i = 0; i < 4; i++) { o[0][i] *= alpha; o[1][i] *= alpha; }
      if (!dry) mbar_wait(sb + B_FULL + 16 * slot + 8, ph);
#pragma unroll
      for (int c = 0; c < 8; c++) {
        uint32_t a0, a1, a2, a3;
        ldsm4t(st + vofs + ((c ^ ri) << 4), a0, a1, a2, a3);
        const uint32_t msk = (c == cm) ? 0x0000ffffu : ((c == (cm ^ 1)) ? 0xffff0000u : 0u);
        mma16816(o[c & 1], a0, a1, a2, a3, pb0 & msk, pb1 & msk);
      }
      if (dry) { dry = false; cur = 0xffffu; mbar_wait(sb + B_Q0, 0); continue; }
      nun++;
      seq++;
      if (cur & INF_FINAL) {
        if (nun == FIN) break;
        __syncwarp();
        if (lane == 0) mbar_arrive(sb + B_EMPTY + 16 * slot + 8);
        if (++slot == NSLOT) { slot = 0; ph ^= 1; }
        continue;
      }
      __syncwarp();
      if (lane == 0) mbar_arrive(sb + B_EMPTY + 16 * slot + 8);
      if (++slot == NSLOT) { slot = 0; ph ^= 1; }
      unsigned nx = lds32v(sb + SM_INFO + 4 * slot);
      if ((nx >> 16) != (seq & 0xffffu)) {
        mbar_wait(sb + B_FULL + 16 * slot, ph);
        nx = lds32v(sb + SM_INFO + 4 * slot);
      }
      nx &= 0xffffu;
      if (nx != cur) {
        float lr = l + __shfl_xor_sync(~0u, l, 1);
        lr += __shfl_xor_sync(~0u, lr, 2);
        mbar_wait(sb + B_FLE + 8 * f, fph);
        const uint32_t base = sb + SM_FL + f * (4 * 528) + warp * 528;
        sts128(base + lane * 16, __float_as_uint(o[0][0] + o[1][0]), __float_as_uint(o[0][1] + o[1][1]),
               __float_as_uint(o[0][2] + o[1][2]), __float_as_uint(o[0][3] + o[1][3]));
        if (lane == 0) sts128(base + 512, __float_as_uint(m), __float_as_uint(lr), cur | (nx & 0x300u), nun);
        __syncwarp();
        if (lane == 0) mbar_arrive(sb + B_FLF + 8 * f);
        if (++f == 2) { f = 0; fph ^= 1; }
      }
    }
    if (owner) {
      float lr = l + __shfl_xor_sync(~0u, l, 1);
      lr += __shfl_xor_sync(~0u, lr, 2);
      const uint32_t v0 = pack_bf16(o[0][0] + o[1][0], o[0][1] + o[1][1]), v1 = pack_bf16(o[0][2] + o[1][2], o[0][3] + o[1][3]);
      const uint32_t dst = sb + SM_XS + ((cta & 1) * 4 + warp) * 272;
#pragma unroll
      for (int rk = 0; rk < 2; rk++) {
        const uint32_t rr = (cta & 1) ^ (rk ^ 1);
        const uint32_t d = mapa(dst, rr), bx = mapa(sb + B_X, rr);
        st_async64(d + lane * 8, v0, v1, bx);
        if (lane == 0) st_async64(d + 256, __float_as_uint(m), __float_as_uint(lr), bx);
      }
      if (tid == 0) TS(12);
    }
  }
  return;
  }

  {
    asm volatile("barrier.cluster.arrive.relaxed.aligned;" ::: "memory");
    asm volatile("bar.sync 2, 96;" ::: "memory");
    if (lane == 0) {
      unsigned grab = cta - NCTA;
      unsigned seq = 1, slot = 1, ph = 1;
      unsigned ls = 0, lph = 0;
      int fin_left = owner ? FIN : 0;
      bool sweeping = true;
      unsigned wake = owner ? ((cta >> 1) + 1) * SW : 0xffffffffu, wake2 = 12 * SW;
      int infl = 2, lim = P_L0;
      while (true) {
        unsigned inf;
        size_t off;
        if (sweeping) {
          const unsigned u = grab + (unsigned)(NSTATIC * NCTA);
          if (u >= wake) { mbar_arrive(sb + B_W); wake = 0xffffffffu; }
          if (u >= wake2) { mbar_arrive(sb + B_W2); wake2 = 0xffffffffu; }
          if (u < (unsigned)SWU) {
            grab = grab_next(sc_->grab);
            const unsigned bh = u / SW;
            off = (size_t)(u + bh * (2 * FIN)) * TILE;
            inf = bh;
          } else {
            sweeping = false;
            lim = P_DF + (P_RK * (u - SWU)) / NCTA;
            TS(10);
          }
        }
        if (!sweeping) {
          if (fin_left == 0) break;
          fin_left--;
          off = (size_t)((cta >> 1) * UPH + SW + 2 * (FIN - 1 - fin_left) + (cta & 1)) * TILE;
          inf = (cta >> 1) | INF_FINAL;
        }
        mbar_wait_n(sb + B_EMPTY + 16 * slot, ph);
        sts32v(sb + SM_INFO + 4 * slot, (seq << 16) | inf);
        while (infl >= lim) {
          mbar_wait_n(sb + B_FULL + 8 * ls, lph);
          if (++ls == NST) { ls = 0; lph ^= 1; }
          infl--;
        }
        infl++;
        mbar_expect_tx(sb + B_FULL + 16 * slot, TILE);
        bulk_load(sb + (2 * slot) * TILE, Kc + off, TILE, sb + B_FULL + 16 * slot, pol);
        if (P_L0 != DEPTH && sweeping) lim = DEPTH;
        mbar_wait_n(sb + B_EMPTY + 16 * slot + 8, ph);
        while (infl >= lim) {
          mbar_wait_n(sb + B_FULL + 8 * ls, lph);
          if (++ls == NST) { ls = 0; lph ^= 1; }
          infl--;
        }
        infl++;
        mbar_expect_tx(sb + B_FULL + 16 * slot + 8, TILE);
        bulk_load(sb + (2 * slot + 1) * TILE, Vc + off, TILE, sb + B_FULL + 16 * slot + 8, pol);
        seq++;
        if (++slot == NSLOT) { slot = 0; ph ^= 1; }
      }
      if (!owner) {
        mbar_wait_n(sb + B_EMPTY + 16 * slot, ph);
        sts32v(sb + SM_INFO + 4 * slot, (seq << 16) | INF_END);
        mbar_arrive(sb + B_FULL + 16 * slot);
      }
    }
    __syncwarp();
    asm volatile("barrier.cluster.wait.acquire.aligned;" ::: "memory");
  }
}

}

extern "C" void kernel_launch(void* const* d_in, const int* in_sizes, int n_in, void* d_out, int out_size) {
  (void)in_sizes; (void)n_in; (void)out_size;
  static bool configured = false;
  static void* scratch = nullptr;
  if (!configured) {
    cudaGetSymbolAddress(&scratch, g_scratch);
    cudaFuncSetAttribute(fused_decode_kernel, cudaFuncAttributeMaxDynamicSharedMemorySize, SM_TOTAL);
    configured = true;
  }
  fused_decode_kernel<<<NCTA, NTHR, SM_TOTAL, cudaStreamPerThread>>>(
      (const char*)d_in[1], (const char*)d_in[2], (Scratch*)scratch, (const __nv_bfloat16*)d_in[0], (const __nv_bfloat16*)d_in[3],
      (const __nv_bfloat16*)d_in[4], (const __nv_bfloat16*)d_in[6], (const __nv_bfloat16*)d_in[7],
      (const __nv_bfloat16*)d_in[8], (const __nv_bfloat16*)d_in[9], (__nv_bfloat16*)d_out);
}
```

```cpp
#include <cuda_runtime.h>
#include <cuda_bf16.h>
#include <stdint.h>

#define P_NST 10
#define P_D 3
#define P_DF 2
#define P_RK 0
#define P_YCLR 1
#define P_SPEC 62
#define P_QCLR 1
#define P_L0 2
#define P_DRY 3
#define P_W0 4
#define P_PS 4
#define P_PF 3
#define P_XCTA 1
#define XWAIT mbar_wait
#define P_PP 250
#define P_PN 2
#define P_FIN 2

namespace {

constexpr int NCTA = 132;
constexpr int NST = P_NST;
constexpr int FIN = P_FIN;
constexpr int UPH = 256;
constexpr int SW = UPH - 2 * FIN;
constexpr int NBH = 64;
constexpr int SWU = NBH * SW;
constexpr int DEPTH = P_D;
constexpr int NSLOT = NST / 2;
constexpr int NSTATIC = 2;
constexpr unsigned GRABS = SWU - NSTATIC * NCTA + NCTA;
constexpr int TILE = 16384;
constexpr int NTHR = 448;
constexpr int NGLU = 43;
constexpr int GLU0 = NCTA - NGLU;
constexpr int DF = 1376;

constexpr int SM_Q = NST * TILE;
constexpr int SM_FL = SM_Q + 16384;
constexpr int SM_XS = SM_FL + 2 * 4 * 528;
constexpr int SM_XS2 = SM_XS + 8 * 272;
constexpr int SM_RED = SM_XS2 + 8 * 272;
constexpr int SM_H = SM_RED + 4096;
constexpr int SM_G = SM_H + 256;
constexpr int SM_BAR = SM_G + 64;
constexpr int B_FULL = SM_BAR;
constexpr int B_EMPTY = B_FULL + 8 * NST;
constexpr int B_FLF = B_EMPTY + 8 * NST;
constexpr int B_FLE = B_FLF + 16;
constexpr int B_Q0 = B_FLE + 16;
constexpr int B_Q1 = B_Q0 + 8;
constexpr int B_X = B_Q1 + 8;
constexpr int B_W = B_X + 8;
constexpr int B_W2 = B_W + 8;
constexpr int B_X0 = B_W2 + 8;
constexpr int B_W3 = B_X0 + 8;
constexpr int SM_INFO = B_W3 + 8;
constexpr int SM_EPOCH = SM_INFO + 4 * 8;
constexpr int SM_TOTAL0 = SM_EPOCH + 16;
constexpr int SM_TOTAL = SM_TOTAL0 < 118 * 1024 ? 118 * 1024 : SM_TOTAL0;

constexpr float M_NONE = -3.0e38f;
constexpr unsigned INF_FINAL = 0x100u;
constexpr unsigned INF_END = 0x200u;

struct __align__(128) Scratch {
  unsigned epoch[1];
  unsigned grab[31];
  unsigned long long qbuf[4096];
  uint2 part[NBH * NCTA * 32];
  uint4 hdr[NBH * NCTA * 2];
  unsigned long long gbuf[NGLU * 1024];
  unsigned long long ybuf[32 * 1024];
};
__device__ Scratch g_scratch;
#define TS(i) do {} while (0)

#define T3X(i) i
constexpr long long SPIN_LIMIT = 2000000000ll;

__device__ __forceinline__ void mbar_init(uint32_t bar, uint32_t cnt) {
  asm volatile("mbarrier.init.shared::cta.b64 [%0], %1;" ::"r"(bar), "r"(cnt) : "memory");
}
__device__ __forceinline__ void mbar_expect_tx(uint32_t bar, uint32_t bytes) {
  asm volatile("mbarrier.arrive.expect_tx.shared::cta.b64 _, [%0], %1;" ::"r"(bar), "r"(bytes) : "memory");
}
__device__ __forceinline__ void mbar_arrive(uint32_t bar) {
  asm volatile("mbarrier.arrive.shared::cta.b64 _, [%0];" ::"r"(bar) : "memory");
}
__device__ __forceinline__ bool mbar_try(uint32_t bar, uint32_t parity) {
  uint32_t ok;
  asm volatile("{\n.reg .pred p;\nmbarrier.try_wait.parity.shared::cta.b64 p, [%1], %2;\nselp.u32 %0, 1, 0, p;\n}\n"
               : "=r"(ok) : "r"(bar), "r"(parity) : "memory");
  return ok != 0;
}
__device__ __forceinline__ void mbar_wait(uint32_t bar, uint32_t parity) {
  if (mbar_try(bar, parity)) return;
  long long t0 = clock64();
  while (!mbar_try(bar, parity)) {
    if (clock64() - t0 > SPIN_LIMIT) __trap();
  }
}
__device__ __forceinline__ void mbar_wait_n(uint32_t bar, uint32_t parity) {
  unsigned n = 0;
  while (!mbar_try(bar, parity))
    if (++n > (1u << 26)) __trap();
}
__device__ __forceinline__ unsigned grab_next(unsigned* ctr) {
  unsigned r;
  asm volatile("atom.relaxed.gpu.global.inc.u32 %0, [%1], %2;" : "=r"(r) : "l"(ctr), "n"(GRABS - 1) : "memory");
  return r;
}
__device__ __forceinline__ bool mbar_try_cluster(uint32_t bar, uint32_t parity) {
  uint32_t ok;
  asm volatile("{\n.reg .pred p;\nmbarrier.try_wait.parity.acquire.cluster.shared::cta.b64 p, [%1], %2;\nselp.u32 %0, 1, 0, p;\n}\n"
               : "=r"(ok) : "r"(bar), "r"(parity) : "memory");
  return ok != 0;
}
__device__ __forceinline__ void mbar_wait_cluster(uint32_t bar, uint32_t parity) {
  if (mbar_try_cluster(bar, parity)) return;
  long long t0 = clock64();
  while (!mbar_try_cluster(bar, parity)) {
    if (clock64() - t0 > SPIN_LIMIT) __trap();
  }
}
__device__ __forceinline__ void bulk_load(uint32_t dst, const void* src, uint32_t bytes, uint32_t bar, uint64_t pol) {
  asm volatile("cp.async.bulk.shared::cluster.global.mbarrier::complete_tx::bytes.L2::cache_hint [%0], [%1], %2, [%3], %4;"
               ::"r"(dst), "l"(src), "r"(bytes), "r"(bar), "l"(pol) : "memory");
}
__device__ __forceinline__ void bulk_prefetch(const void* src, uint32_t bytes) {
  asm volatile("cp.async.bulk.prefetch.L2.global [%0], %1;" ::"l"(src), "r"(bytes) : "memory");
}
__device__ __forceinline__ void ldsm4(uint32_t addr, uint32_t& a0, uint32_t& a1, uint32_t& a2, uint32_t& a3) {
  asm volatile("ldmatrix.sync.aligned.m8n8.x4.shared.b16 {%0,%1,%2,%3}, [%4];"
               : "=r"(a0), "=r"(a1), "=r"(a2), "=r"(a3) : "r"(addr) : "memory");
}
__device__ __forceinline__ void ldsm4t(uint32_t addr, uint32_t& a0, uint32_t& a1, uint32_t& a2, uint32_t& a3) {
  asm volatile("ldmatrix.sync.aligned.m8n8.x4.trans.shared.b16 {%0,%1,%2,%3}, [%4];"
               : "=r"(a0), "=r"(a1), "=r"(a2), "=r"(a3) : "r"(addr) : "memory");
}
__device__ __forceinline__ void mma16816(float (&c)[4], uint32_t a0, uint32_t a1, uint32_t a2, uint32_t a3, uint32_t b0, uint32_t b1) {
  asm volatile("mma.sync.aligned.m16n8k16.row.col.f32.bf16.bf16.f32 {%0,%1,%2,%3}, {%4,%5,%6,%7}, {%8,%9}, {%0,%1,%2,%3};"
               : "+f"(c[0]), "+f"(c[1]), "+f"(c[2]), "+f"(c[3]) : "r"(a0), "r"(a1), "r"(a2), "r"(a3), "r"(b0), "r"(b1));
}
__device__ __forceinline__ uint32_t lds32(uint32_t a) { uint32_t v; asm volatile("ld.shared.b32 %0, [%1];" : "=r"(v) : "r"(a) : "memory"); return v; }
__device__ __forceinline__ uint32_t lds32v(uint32_t a) { uint32_t v; asm volatile("ld.volatile.shared.b32 %0, [%1];" : "=r"(v) : "r"(a) : "memory"); return v; }
__device__ __forceinline__ float2 lds64f(uint32_t a) { float2 v; asm volatile("ld.shared.v2.f32 {%0,%1}, [%2];" : "=f"(v.x), "=f"(v.y) : "r"(a) : "memory"); return v; }
__device__ __forceinline__ uint4 lds128(uint32_t a) { uint4 v; asm volatile("ld.shared.v4.b32 {%0,%1,%2,%3}, [%4];" : "=r"(v.x), "=r"(v.y), "=r"(v.z), "=r"(v.w) : "r"(a) : "memory"); return v; }
__device__ __forceinline__ void sts32(uint32_t a, uint32_t v) { asm volatile("st.shared.b32 [%0], %1;" ::"r"(a), "r"(v) : "memory"); }
__device__ __forceinline__ void sts32v(uint32_t a, uint32_t v) { asm volatile("st.volatile.shared.b32 [%0], %1;" ::"r"(a), "r"(v) : "memory"); }
__device__ __forceinline__ void sts64(uint32_t a, uint32_t x, uint32_t y) { asm volatile("st.shared.v2.b32 [%0], {%1,%2};" ::"r"(a), "r"(x), "r"(y) : "memory"); }
__device__ __forceinline__ void sts128(uint32_t a, uint32_t x, uint32_t y, uint32_t z, uint32_t w) { asm volatile("st.shared.v4.b32 [%0], {%1,%2,%3,%4};" ::"r"(a), "r"(x), "r"(y), "r"(z), "r"(w) : "memory"); }
__device__ __forceinline__ uint32_t pack_bf16(float lo, float hi) {
  uint32_t r; asm("cvt.rn.bf16x2.f32 %0, %1, %2;" : "=r"(r) : "f"(hi), "f"(lo)); return r;
}
__device__ __forceinline__ float bf_lo(uint32_t v) { return __uint_as_float(v << 16); }
__device__ __forceinline__ float bf_hi(uint32_t v) { return __uint_as_float(v & 0xffff0000u); }
__device__ __forceinline__ float bf_round(float v) { return __bfloat162float(__float2bfloat16_rn(v)); }
__device__ __forceinline__ float ex2(float v) { float r; asm("ex2.approx.ftz.f32 %0, %1;" : "=f"(r) : "f"(v)); return r; }
__device__ __forceinline__ void aux_bar() { asm volatile("bar.sync 1, 256;" ::: "memory"); }
__device__ __forceinline__ uint4 ldg128(const void* p) {
  uint4 v; asm volatile("ld.global.nc.v4.b32 {%0,%1,%2,%3}, [%4];" : "=r"(v.x), "=r"(v.y), "=r"(v.z), "=r"(v.w) : "l"(p)); return v;
}
__device__ __forceinline__ uint2 ldg64(const void* p) {
  uint2 v; asm volatile("ld.global.nc.v2.b32 {%0,%1}, [%2];" : "=r"(v.x), "=r"(v.y) : "l"(p)); return v;
}
__device__ __forceinline__ uint4 ld_relaxed128(const void* p) {
  unsigned long long a, b;
  asm volatile("ld.relaxed.gpu.global.v2.b64 {%0,%1}, [%2];" : "=l"(a), "=l"(b) : "l"(p) : "memory");
  return make_uint4((uint32_t)a, (uint32_t)(a >> 32), (uint32_t)b, (uint32_t)(b >> 32));
}
__device__ __forceinline__ uint2 ld_relaxed64(const void* p) {
  unsigned long long a;
  asm volatile("ld.relaxed.gpu.global.b64 %0, [%1];" : "=l"(a) : "l"(p) : "memory");
  return make_uint2((uint32_t)a, (uint32_t)(a >> 32));
}
__device__ __forceinline__ void st_relaxed64(void* p, uint32_t lo, uint32_t hi) {
  unsigned long long a = ((unsigned long long)hi << 32) | lo;
  asm volatile("st.relaxed.gpu.global.b64 [%0], %1;" ::"l"(p), "l"(a) : "memory");
}
__device__ __forceinline__ void st_relaxed128(void* p, uint32_t lo0, uint32_t hi0, uint32_t lo1, uint32_t hi1) {
  unsigned long long a = ((unsigned long long)hi0 << 32) | lo0, b = ((unsigned long long)hi1 << 32) | lo1;
  asm volatile("st.relaxed.gpu.global.v2.b64 [%0], {%1,%2};" ::"l"(p), "l"(a), "l"(b) : "memory");
}
__device__ __forceinline__ uint4 ldcg128(const void* p) {
  uint4 v; asm volatile("ld.global.cg.v4.b32 {%0,%1,%2,%3}, [%4];" : "=r"(v.x), "=r"(v.y), "=r"(v.z), "=r"(v.w) : "l"(p) : "memory"); return v;
}
__device__ __forceinline__ void st_async64(uint32_t addr, uint32_t x, uint32_t y, uint32_t bar) {
  asm volatile("st.async.shared::cluster.mbarrier::complete_tx::bytes.v2.b32 [%0], {%1,%2}, [%3];" ::"r"(addr), "r"(x), "r"(y), "r"(bar) : "memory");
}
__device__ __forceinline__ uint32_t mapa(uint32_t addr, uint32_t rank) {
  uint32_t r; asm("mapa.shared::cluster.u32 %0, %1, %2;" : "=r"(r) : "r"(addr), "r"(rank)); return r;
}

__device__ __forceinline__ void gemv32_reduce(const uint4 (&w)[8], const uint4& x0, const uint4& x1, uint32_t red, int warp, int lane) {
  float a0[8], a1[8];
#pragma unroll
  for (int j = 0; j < 8; j++) { a0[j] = 0.f; a1[j] = 0.f; }
  const uint32_t xa[4] = {x0.x, x0.y, x0.z, x0.w}, xb[4] = {x1.x, x1.y, x1.z, x1.w};
#pragma unroll
  for (int j = 0; j < 8; j++) {
    const float fa = (j & 1) ? bf_hi(xa[j >> 1]) : bf_lo(xa[j >> 1]);
    const float fb = (j & 1) ? bf_hi(xb[j >> 1]) : bf_lo(xb[j >> 1]);
    const uint32_t ww[4] = {w[j].x, w[j].y, w[j].z, w[j].w};
#pragma unroll
    for (int i = 0; i < 4; i++) {
      const float lo = bf_lo(ww[i]), hi = bf_hi(ww[i]);
      a0[2 * i] = fmaf(fa, lo, a0[2 * i]); a0[2 * i + 1] = fmaf(fa, hi, a0[2 * i + 1]);
      a1[2 * i] = fmaf(fb, lo, a1[2 * i]); a1[2 * i + 1] = fmaf(fb, hi, a1[2 * i + 1]);
    }
  }
  const bool b4 = lane & 16, b3 = lane & 8, b2 = lane & 4;
  float v[8];
#pragma unroll
  for (int j = 0; j < 8; j++) v[j] = (b4 ? a1[j] : a0[j]) + __shfl_xor_sync(~0u, b4 ? a0[j] : a1[j], 16);
  float u[4];
#pragma unroll
  for (int j = 0; j < 4; j++) u[j] = (b3 ? v[j + 4] : v[j]) + __shfl_xor_sync(~0u, b3 ? v[j] : v[j + 4], 8);
  const float r0 = (b2 ? u[2] : u[0]) + __shfl_xor_sync(~0u, b2 ? u[0] : u[2], 4);
  const float r1 = (b2 ? u[3] : u[1]) + __shfl_xor_sync(~0u, b2 ? u[1] : u[3], 4);
  const int idx = (b4 ? 32 : 0) + (lane & 3) * 8 + (b3 ? 4 : 0) + (b2 ? 2 : 0);
  sts64(red + (warp * 64 + idx) * 4, __float_as_uint(r0), __float_as_uint(r1));
}
__device__ __forceinline__ float2 gemv32_final(uint32_t red, int i  ) {
  float2 s = make_float2(0.f, 0.f);
#pragma unroll
  for (int w = 0; w < 8; w++) { float2 v = lds64f(red + (w * 64 + 2 * i) * 4); s.x += v.x; s.y += v.y; }
  return s;
}

__device__ __forceinline__ void wo_mma(const uint32_t (&A)[8][8], uint32_t slot, int g, int t, float (&c)[4][4]) {
  uint4 bv[4];
#pragma unroll
  for (int j = 0; j < 4; j++) bv[j] = lds128(slot + g * 272 + t * 64 + ((j ^ ((t >> 1) << 1)) << 4));
#pragma unroll
  for (int i = 0; i < 4; i++) { c[i][0] = 0.f; c[i][1] = 0.f; c[i][2] = 0.f; c[i][3] = 0.f; }
#pragma unroll
  for (int j = 0; j < 4; j++) {
    mma16816(c[0], A[2 * j][0], A[2 * j][1], A[2 * j][2], A[2 * j][3], bv[j].x, bv[j].y);
    mma16816(c[1], A[2 * j][4], A[2 * j][5], A[2 * j][6], A[2 * j][7], bv[j].x, bv[j].y);
    mma16816(c[2], A[2 * j + 1][0], A[2 * j + 1][1], A[2 * j + 1][2], A[2 * j + 1][3], bv[j].z, bv[j].w);
    mma16816(c[3], A[2 * j + 1][4], A[2 * j + 1][5], A[2 * j + 1][6], A[2 * j + 1][7], bv[j].z, bv[j].w);
  }
}
__device__ __forceinline__ void wo_mma2(const uint32_t (&A)[8][8], uint32_t xa, uint32_t xb, float (&c)[4][4]) {
  uint4 bv[4];
#pragma unroll
  for (int j = 0; j < 4; j++) bv[j] = lds128((j < 2 ? xa : xb) + (j & 1) * 16);
#pragma unroll
  for (int i = 0; i < 4; i++) { c[i][0] = 0.f; c[i][1] = 0.f; c[i][2] = 0.f; c[i][3] = 0.f; }
#pragma unroll
  for (int j = 0; j < 4; j++) {
    mma16816(c[0], A[2 * j][0], A[2 * j][1], A[2 * j][2], A[2 * j][3], bv[j].x, bv[j].y);
    mma16816(c[1], A[2 * j][4], A[2 * j][5], A[2 * j][6], A[2 * j][7], bv[j].x, bv[j].y);
    mma16816(c[2], A[2 * j + 1][0], A[2 * j + 1][1], A[2 * j + 1][2], A[2 * j + 1][3], bv[j].z, bv[j].w);
    mma16816(c[3], A[2 * j + 1][4], A[2 * j + 1][5], A[2 * j + 1][6], A[2 * j + 1][7], bv[j].z, bv[j].w);
  }
}
__device__ __forceinline__ void wo_weight(const float (&c)[4][4], float w0, float w1, float (&y)[4]) {
  y[0] = fmaf(w0, c[0][0] + c[2][0], fmaf(w1, c[0][1] + c[2][1], y[0]));
  y[1] = fmaf(w0, c[0][2] + c[2][2], fmaf(w1, c[0][3] + c[2][3], y[1]));
  y[2] = fmaf(w0, c[1][0] + c[3][0], fmaf(w1, c[1][1] + c[3][1], y[2]));
  y[3] = fmaf(w0, c[1][2] + c[3][2], fmaf(w1, c[1][3] + c[3][3], y[3]));
}
__device__ __forceinline__ float wo_reduce(const float (&y)[4], int t) {
  const float y0 = y[0], y1 = y[1], y2 = y[2], y3 = y[3];
  const bool b1 = t & 2, b0 = t & 1;
  const float z0 = (b1 ? y2 : y0) + __shfl_xor_sync(~0u, b1 ? y0 : y2, 2);
  const float z1 = (b1 ? y3 : y1) + __shfl_xor_sync(~0u, b1 ? y1 : y3, 2);
  return (b0 ? z1 : z0) + __shfl_xor_sync(~0u, b0 ? z0 : z1, 1);
}

__global__ void __cluster_dims__(2, 1, 1) __launch_bounds__(NTHR, 1)
fused_decode_kernel(const char* __restrict__ Kc, const char* __restrict__ Vc, Scratch* sc_,
                    const __nv_bfloat16* __restrict__ x, const __nv_bfloat16* __restrict__ wq,
                    const __nv_bfloat16* __restrict__ wo,
                    const __nv_bfloat16* __restrict__ wg, const __nv_bfloat16* __restrict__ wu,
                    const __nv_bfloat16* __restrict__ wd, const __nv_bfloat16* __restrict__ gw,
                    __nv_bfloat16* __restrict__ out) {
  extern __shared__ __align__(1024) unsigned char smem_raw[];
  const uint32_t sb = (uint32_t)__cvta_generic_to_shared(smem_raw);
  const int tid = threadIdx.x, warp = tid >> 5, lane = tid & 31;
  const int cta = blockIdx.x;
  const bool owner = cta < 128;
  uint64_t pol;
  asm volatile("createpolicy.fractional.L2::evict_first.b64 %0, 1.0;" : "=l"(pol));
  unsigned epoch = 0;
  if (warp == 1) asm volatile("ld.relaxed.gpu.global.u32 %0, [%1];" : "=r"(epoch) : "l"(&sc_->epoch[0]) : "memory");
  if (tid == 0) {
    mbar_init(sb + B_FULL, 1);
    mbar_init(sb + B_FULL + 8, 1);
    asm volatile("fence.proxy.async.shared::cta;" ::: "memory");
    mbar_expect_tx(sb + B_FULL, TILE);
    bulk_load(sb, Kc + (size_t)cta * TILE, TILE, sb + B_FULL, pol);
    mbar_expect_tx(sb + B_FULL + 8, TILE);
    bulk_load(sb + TILE, Vc + (size_t)cta * TILE, TILE, sb + B_FULL + 8, pol);
  }

  if ((P_PF & 1) && tid == 64 && owner) bulk_prefetch(wq + (size_t)cta * 16384, 32768);

  if (warp >= 6) {
    const int at = tid - 192, aw = warp - 6;
    const int g = lane >> 2, t = lane & 3;
    uint4 w[8];
    const int rg = at >> 2, cq = at & 3;
    asm volatile("barrier.cluster.arrive.relaxed.aligned;" ::: "memory");
#pragma unroll
    for (int j = 0; j < 8; j++) {
      w[j] = make_uint4(0, 0, 0, 0);
      if (owner) w[j] = ldg128(wq + (size_t)(rg * 8 + j) * 4096 + cta * 32 + cq * 8);
    }
    const uint4 x0 = ldg128(x + rg * 8), x1 = ldg128(x + 512 + rg * 8);
    if (owner || (P_DRY & 2)) gemv32_reduce(w, x0, x1, sb + SM_RED, aw, lane);
    asm volatile("barrier.cluster.wait.acquire.aligned;" ::: "memory");
    const uint32_t tag = lds32(sb + SM_EPOCH) + 1u;
    aux_bar();
    if (at < 32) {
      const float2 s = gemv32_final(sb + SM_RED, at);
      if (owner) st_relaxed64(&sc_->qbuf[(at >> 4) * 2048 + cta * 16 + (at & 15)], pack_bf16(s.x, s.y), tag);
    }
    if ((P_PF & 2) && at == 64 && cta >= GLU0) {
      bulk_prefetch(wg + (size_t)(cta - GLU0) * 16384, 32768);
      bulk_prefetch(wu + (size_t)(cta - GLU0) * 16384, 32768);
    }
    if (at == 0) TS(1);
    if (at < 64) {
      long long t0 = clock64();
      uint4 v = ld_relaxed128(&sc_->qbuf[at * 2]);
      while (v.y != tag || v.w != tag) {
        if (clock64() - t0 > SPIN_LIMIT) __trap();
        v = ld_relaxed128(&sc_->qbuf[at * 2]);
      }
      sts64(sb + SM_Q + at * 8, v.x, v.z);
      __syncwarp();
      if (lane == 0) mbar_arrive(sb + B_Q0);
    }
    if (at == 0) TS(2);
    aux_bar();
    {
      uint4 v[8];
#pragma unroll
      for (int j = 0; j < 8; j++) v[j] = ld_relaxed128(&sc_->qbuf[(j * 256 + at) * 2]);
      long long t0 = clock64();
#pragma unroll
      for (int j = 0; j < 8; j++) {
        while (v[j].y != tag || v[j].w != tag) {
          if (clock64() - t0 > SPIN_LIMIT) __trap();
          v[j] = ld_relaxed128(&sc_->qbuf[(j * 256 + at) * 2]);
        }
        if (j > 0 || at >= 64) sts64(sb + SM_Q + (j * 256 + at) * 8, v[j].x, v[j].z);
      }
      __syncwarp();
      if (lane == 0) mbar_arrive(sb + B_Q1);
    }
    if (at == 0) TS(3);
    if (cta >= GLU0) {
      const int f = cta - GLU0;
      uint4 w2[8];
#pragma unroll
      for (int j = 0; j < 8; j++) w[j] = ldg128(wg + (size_t)(rg * 8 + j) * DF + f * 32 + cq * 8);
#pragma unroll
      for (int j = 0; j < 8; j++) w2[j] = ldg128(wu + (size_t)(rg * 8 + j) * DF + f * 32 + cq * 8);
      gemv32_reduce(w, x0, x1, sb + SM_RED, aw, lane);
      const int dr = lane >> 3, dc = aw * 64 + (lane & 7) * 8;
#pragma unroll
      for (int j = 0; j < 8; j++) w[j] = ldg128(wd + (size_t)(f * 32 + dr * 8 + j) * 512 + dc);
      gemv32_reduce(w2, x0, x1, sb + SM_RED + 2048, aw, lane);
      aux_bar();
      if (at < 32) {
        const float2 gs = gemv32_final(sb + SM_RED, at), us = gemv32_final(sb + SM_RED + 2048, at);
        float hh[2];
#pragma unroll
        for (int i = 0; i < 2; i++) {
          const float gv = bf_round(i ? gs.y : gs.x), uv = bf_round(i ? us.y : us.x);
          const float inner = 0.7978845608028654f * (gv + 0.044715f * gv * gv * gv);
          const float ge = bf_round(0.5f * gv * (1.f + tanhf(inner)));
          hh[i] = bf_round(ge * uv);
        }
        sts64(sb + SM_H + at * 8, __float_as_uint(hh[0]), __float_as_uint(hh[1]));
      }
      aux_bar();
      float a0[8], a1[8];
#pragma unroll
      for (int j = 0; j < 8; j++) { a0[j] = 0.f; a1[j] = 0.f; }
#pragma unroll
      for (int j = 0; j < 8; j++) {
        const float fa = __uint_as_float(lds32(sb + SM_H + (dr * 8 + j) * 4));
        const float fb = __uint_as_float(lds32(sb + SM_H + (32 + dr * 8 + j) * 4));
        const uint32_t ww[4] = {w[j].x, w[j].y, w[j].z, w[j].w};
#pragma unroll
        for (int i = 0; i < 4; i++) {
          const float lo = bf_lo(ww[i]), hi = bf_hi(ww[i]);
          a0[2 * i] = fmaf(fa, lo, a0[2 * i]); a0[2 * i + 1] = fmaf(fa, hi, a0[2 * i + 1]);
          a1[2 * i] = fmaf(fb, lo, a1[2 * i]); a1[2 * i + 1] = fmaf(fb, hi, a1[2 * i + 1]);
        }
      }
      const bool b4 = lane & 16, b3 = lane & 8;
      float v[8], u[4];
#pragma unroll
      for (int j = 0; j < 8; j++) v[j] = (b4 ? a1[j] : a0[j]) + __shfl_xor_sync(~0u, b4 ? a0[j] : a1[j], 16);
#pragma unroll
      for (int j = 0; j < 4; j++) u[j] = (b3 ? v[j + 4] : v[j]) + __shfl_xor_sync(~0u, b3 ? v[j] : v[j + 4], 8);
      unsigned long long* dst = &sc_->gbuf[f * 1024 + (b4 ? 512 : 0) + dc + (b3 ? 4 : 0)];
      st_relaxed128(dst, __float_as_uint(u[0]), tag, __float_as_uint(u[1]), tag);
      st_relaxed128(dst + 2, __float_as_uint(u[2]), tag, __float_as_uint(u[3]), tag);
    }
    if (!owner) return;
    mbar_wait(sb + B_W3, 0);
    const int bh = cta >> 1, r = cta & 1, h = bh & 31, b = bh >> 5;
    const int n0 = 256 * r + 32 * aw;
    uint32_t A[8][8];
#pragma unroll
    for (int ks = 0; ks < 8; ks++) {
      const int L = 8 * t + (ks ^ ((t >> 1) << 2));
      const int d0 = 16 * (L & 3) + (L >> 2);
      const __nv_bfloat16* p = wo + (size_t)(h * 128 + d0) * 512 + n0 + 4 * g;
      const uint2 v0 = ldg64(p), v1 = ldg64(p + 8 * 512), v2 = ldg64(p + 64 * 512), v3 = ldg64(p + 72 * 512);
      A[ks][0] = __byte_perm(v0.x, v1.x, 0x5410); A[ks][1] = __byte_perm(v0.x, v1.x, 0x7632);
      A[ks][2] = __byte_perm(v2.x, v3.x, 0x5410); A[ks][3] = __byte_perm(v2.x, v3.x, 0x7632);
      A[ks][4] = __byte_perm(v0.y, v1.y, 0x5410); A[ks][5] = __byte_perm(v0.y, v1.y, 0x7632);
      A[ks][6] = __byte_perm(v2.y, v3.y, 0x5410); A[ks][7] = __byte_perm(v2.y, v3.y, 0x7632);
    }
    const int oi = cta * 8 + aw;
    unsigned long long* const ydst = &sc_->ybuf[((b * 512 + n0 + lane) >> 3) * 256 + h * 8 + (lane & 7)];
    {
      const int ob = oi >> 9;
      float s = 0.f;
#pragma unroll
      for (int j = 0; j < 2; j++) {
        const uint4 xv = ldg128(x + ob * 512 + j * 256 + lane * 8), gv = ldg128(gw + j * 256 + lane * 8);
        const uint32_t xx[4] = {xv.x, xv.y, xv.z, xv.w}, gg[4] = {gv.x, gv.y, gv.z, gv.w};
#pragma unroll
        for (int i = 0; i < 4; i++) s += bf_round(bf_lo(xx[i]) * bf_lo(gg[i])) + bf_round(bf_hi(xx[i]) * bf_hi(gg[i]));
      }
      if (P_YCLR) st_relaxed64(ydst, 0u, tag - 1u);
      mbar_wait(sb + B_W2, 0);
      float bs = 0.f;
      long long t0 = clock64();
#pragma unroll
      for (int j = 0; j < 2; j++) {
        const int f = j * 32 + lane;
        if (f < NGLU) {
          uint2 v = ld_relaxed64(&sc_->gbuf[f * 1024 + oi]);
          while (v.y != tag) {
            if (clock64() - t0 > SPIN_LIMIT) __trap();
            __nanosleep(200);
            v = ld_relaxed64(&sc_->gbuf[f * 1024 + oi]);
          }
          bs += __uint_as_float(v.x);
        }
      }
#pragma unroll
      for (int o = 16; o > 0; o >>= 1) { s += __shfl_xor_sync(~0u, s, o); bs += __shfl_xor_sync(~0u, bs, o); }
      s = bf_round(s);
      const float gate = bf_round(1.f / (1.f + expf(-s)));
      const float gluterm = bf_round(bf_round(1.f - gate) * bf_round(bs));
      if (lane == 0) sts64(sb + SM_G + aw * 8, __float_as_uint(gate), __float_as_uint(gluterm));
    }
    if (at == 0) TS(4);
    {
      const uint32_t xa = sb + SM_XS + g * 272 + t * 64;
      sts128(sb + SM_RED + at * 16, (uint32_t)(size_t)ydst, (uint32_t)((size_t)ydst >> 32), xa + (t >> 1) * 32, xa + 32 - (t >> 1) * 32);
    }
    mbar_wait(sb + B_W, 0);
    {
      const int pg = at >> 4, c16 = at & 15;
      const int hi = (lane >> 1) * 16 + 2 * aw + (lane & 1);
      uint4 hd, pv[9];
      const uint2* part = sc_->part + (size_t)bh * (NCTA * 32);
      const uint32_t par = tag & 1u;
      bool ldd = bh >= P_SPEC;
      hd = make_uint4(__float_as_uint(M_NONE), hi < NCTA ? tag - 1u : tag, 0u, tag);
#pragma unroll
      for (int k = 0; k < 9; k++) pv[k] = make_uint4(k * 16 + pg < NCTA ? par ^ 1u : par, 0, par, 0);
      for (unsigned n = 0;; n++) {
        if (hd.y != tag || hd.w != tag) hd = ld_relaxed128(&sc_->hdr[(bh * NCTA + hi) * 2]);
#pragma unroll
        for (int k = 0; k < 9; k++)
          if (ldd && (((pv[k].x ^ par) | (pv[k].z ^ par)) & 1u)) pv[k] = ld_relaxed128(part + (k * 16 + pg) * 32 + c16 * 2);
        uint32_t bad = 0;
#pragma unroll
        for (int k = 0; k < 9; k++) bad |= (pv[k].x ^ par) | (pv[k].z ^ par);
        const bool hok = __all_sync(~0u, hd.y == tag && hd.w == tag);
        if (hok && !__any_sync(~0u, bad & 1u)) break;
        if (hok) ldd = true;
        if (n > (1u << 22)) __trap();
      }
      int mi = (int)hd.x;
      mi ^= (mi >> 31) & 0x7fffffff;
      mi = __reduce_max_sync(~0u, mi);
      mi ^= (mi >> 31) & 0x7fffffff;
      const float m = __int_as_float(mi);
      const float e = ex2(__uint_as_float(hd.x) - m);
      float l = e * __uint_as_float(hd.z);
#pragma unroll
      for (int o = 16; o > 0; o >>= 1) l += __shfl_xor_sync(~0u, l, o);
      float acc[8];
#pragma unroll
      for (int j = 0; j < 8; j++) acc[j] = 0.f;
#pragma unroll
      for (int k = 0; k < 9; k++) {
        const float wk = __shfl_sync(~0u, e, 2 * k + (lane >> 4));
        const uint32_t pp[4] = {pv[k].x, pv[k].y, pv[k].z, pv[k].w};
#pragma unroll
        for (int i = 0; i < 4; i++) {
          acc[2 * i] = fmaf(wk, bf_lo(pp[i]), acc[2 * i]);
          acc[2 * i + 1] = fmaf(wk, bf_hi(pp[i]), acc[2 * i + 1]);
        }
      }
#pragma unroll
      for (int j = 0; j < 8; j++) acc[j] += __shfl_xor_sync(~0u, acc[j], 16);
      if (lane < 16)
        sts128(sb + SM_XS2 + aw * 272 + c16 * 16, pack_bf16(acc[0], acc[1]), pack_bf16(acc[2], acc[3]),
               pack_bf16(acc[4], acc[5]), pack_bf16(acc[6], acc[7]));
      if (lane == 0) sts64(sb + SM_XS2 + aw * 272 + 256, __float_as_uint(m), __float_as_uint(l));
      aux_bar();
      if (at == 0) { TS(T3X(5)); if (cta == 0) asm volatile("st.relaxed.gpu.global.u32 [%0], %1;" ::"l"(&sc_->epoch[0]), "r"(tag) : "memory"); }
    }
    {
      const float2 s0 = lds64f(sb + SM_XS2 + (2 * t) * 272 + 256), s1 = lds64f(sb + SM_XS2 + (2 * t + 1) * 272 + 256);
      float c[4][4];
      wo_mma(A, sb + SM_XS2, g, t, c);
      XWAIT(sb + B_X0, 0);
      const float2 h0 = lds64f(sb + SM_XS + (2 * t) * 272 + 256), h1 = lds64f(sb + SM_XS + (2 * t + 1) * 272 + 256);
      float M = fmaxf(fmaxf(h0.x, h1.x), fmaxf(s0.x, s1.x));
      M = fmaxf(M, __shfl_xor_sync(~0u, M, 1));
      M = fmaxf(M, __shfl_xor_sync(~0u, M, 2));
      float e0 = ex2(h0.x - M), e1 = ex2(h1.x - M);
      const float f0 = ex2(s0.x - M), f1 = ex2(s1.x - M);
      float L = (e0 * h0.y + e1 * h1.y) + (f0 * s0.y + f1 * s1.y);
      L += __shfl_xor_sync(~0u, L, 1);
      L += __shfl_xor_sync(~0u, L, 2);
      float y[4] = {0.f, 0.f, 0.f, 0.f};
      wo_weight(c, f0, f1, y);
      const float rl = __fdividef(1.f, L);
      if (at == 0) TS(T3X(6));
      const uint4 pk = lds128(sb + SM_RED + at * 16);
      XWAIT(sb + B_X, 0);
      if (at == 0) TS(T3X(7));
      wo_mma2(A, pk.z, pk.w, c);
      wo_weight(c, e0, e1, y);
      st_relaxed64((void*)(((size_t)pk.y << 32) | pk.x), __float_as_uint(rl * wo_reduce(y, t)), tag);
    }
    if (at == 0) TS(8);
    if (aw == 0) {
      const int e = 2 * t + (g & 1);
      const float2 gg = lds64f(sb + SM_G + e * 8);
      const unsigned long long* p = &sc_->ybuf[cta * 256 + lane * 2];
      uint4 v[P_PN][4];
#pragma unroll
      for (int k = 0; k < P_PN; k++) {
        if (k) { const unsigned c0 = clock(); while (clock() - c0 < P_PP) {} }
#pragma unroll
        for (int j = 0; j < 4; j++) v[k][j] = ld_relaxed128(p + j * 64);
      }
      float s0, s1;
      for (unsigned n = 0;; n++) {
        bool done = false;
#pragma unroll
        for (int k = 0; k < P_PN; k++) {
          uint32_t bad = 0;
#pragma unroll
          for (int j = 0; j < 4; j++) bad |= (v[k][j].y ^ tag) | (v[k][j].w ^ tag);
          s0 = (__uint_as_float(v[k][0].x) + __uint_as_float(v[k][1].x)) + (__uint_as_float(v[k][2].x) + __uint_as_float(v[k][3].x));
          s1 = (__uint_as_float(v[k][0].z) + __uint_as_float(v[k][1].z)) + (__uint_as_float(v[k][2].z) + __uint_as_float(v[k][3].z));
          if (!__any_sync(~0u, bad)) { done = true; break; }
#pragma unroll
          for (int j = 0; j < 4; j++) v[k][j] = ld_relaxed128(p + j * 64);
        }
        if (done) break;
        if (n > (1u << 21)) __trap();
      }
      float a = ((g & 1) ? s1 : s0) + __shfl_xor_sync(~0u, (g & 1) ? s0 : s1, 4);
      a += __shfl_xor_sync(~0u, a, 8);
      a += __shfl_xor_sync(~0u, a, 16);
      if (lane < 8) out[cta * 8 + e] = __float2bfloat16_rn(bf_round(gg.x * bf_round(a)) + gg.y);
      if (lane == 0) TS(9);
    }
    return;
  }

  if (warp != 4) {
  if (warp == 5) {
    if (lane == 0) {
#pragma unroll
      for (int s = 2; s < NST; s++) mbar_init(sb + B_FULL + 8 * s, 1);
#pragma unroll
      for (int s = 0; s < NST; s++) mbar_init(sb + B_EMPTY + 8 * s, 4);
      mbar_init(sb + B_W, 1); mbar_init(sb + B_W2, 1); mbar_init(sb + B_W3, 1);
      mbar_init(sb + B_FLF, 4); mbar_init(sb + B_FLF + 8, 4); mbar_init(sb + B_FLE, 1); mbar_init(sb + B_FLE + 8, 1);
      mbar_init(sb + B_Q0, 2); mbar_init(sb + B_Q1, 8); mbar_init(sb + B_X, 1); mbar_init(sb + B_X0, 1);
      mbar_expect_tx(sb + B_X, 8 * 256);
      mbar_expect_tx(sb + B_X0, 8 * 8);
#pragma unroll
      for (int n = 0; n < NSLOT; n++)
        sts32v(sb + SM_INFO + 4 * n, n == 0 ? 0u : 0xffffffffu);
      asm volatile("fence.mbarrier_init.release.cluster;" ::: "memory");
      asm volatile("fence.proxy.async.shared::cta;" ::: "memory");
    }
  } else if (warp == 1) {
    if (lane == 0) sts32(sb + SM_EPOCH, epoch);
    if (P_QCLR && owner) st_relaxed64(&sc_->qbuf[(lane >> 4) * 2048 + cta * 16 + (lane & 15)], 0u, epoch);
  }
  __syncwarp();
  if (warp == 0 || warp == 5) asm volatile("bar.arrive 2, 96;" ::: "memory");
  asm volatile("fence.acq_rel.cta;" ::: "memory");
  asm volatile("barrier.cluster.arrive.relaxed.aligned;\nbarrier.cluster.wait.acquire.aligned;" ::: "memory");

  if (warp == 5) {
    const uint32_t tag = lds32(sb + SM_EPOCH) + 1u;
    const uint32_t par = tag & 1u;
    unsigned f = 0, ph = 0, nexth = 0;
    while (true) {
      mbar_wait(sb + B_FLF + 8 * f, ph);
      const uint32_t base = sb + SM_FL + f * (4 * 528);
      const uint4 meta = lds128(base + 512);
      float mj[4], lj[4];
      uint4 oj[4];
#pragma unroll
      for (int j = 0; j < 4; j++) {
        const float2 hh = lds64f(base + j * 528 + 512);
        mj[j] = hh.x; lj[j] = hh.y;
        oj[j] = lds128(base + j * 528 + lane * 16);
      }
      __syncwarp();
      if (lane == 0) mbar_arrive(sb + B_FLE + 8 * f);
      const float M = fmaxf(fmaxf(mj[0], mj[1]), fmaxf(mj[2], mj[3]));
      float o0 = 0.f, o1 = 0.f, o2 = 0.f, o3 = 0.f, L = 0.f;
#pragma unroll
      for (int j = 0; j < 4; j++) {
        const float e = ex2(mj[j] - M);
        L = fmaf(e, lj[j], L);
        o0 = fmaf(e, __uint_as_float(oj[j].x), o0); o1 = fmaf(e, __uint_as_float(oj[j].y), o1);
        o2 = fmaf(e, __uint_as_float(oj[j].z), o2); o3 = fmaf(e, __uint_as_float(oj[j].w), o3);
      }
      const unsigned bh = meta.z & 0xffu;
      const uint32_t b0 = __float_as_uint(o0);
      const uint32_t r0 = par ? ((b0 >> 16) | 1u) : (((b0 + 0x10000u) >> 16) & 0xfffeu);
      const uint32_t w0 = (pack_bf16(0.f, o1) & 0xffff0000u) | r0;
      st_relaxed64(sc_->part + (size_t)(bh * NCTA + cta) * 32 + lane, w0, pack_bf16(o2, o3));
      if (lane < 2) st_relaxed128(&sc_->hdr[(bh * NCTA + cta) * 2 + lane], __float_as_uint(M), tag, __float_as_uint(L), tag);
      const bool last = meta.z & 0x300u;
      for (; nexth < (last ? (unsigned)NBH : bh); nexth++)
        if (nexth != bh) {
          st_relaxed64(sc_->part + (size_t)(nexth * NCTA + cta) * 32 + lane, par, 0u);
          if (lane < 2) st_relaxed128(&sc_->hdr[(nexth * NCTA + cta) * 2 + lane], __float_as_uint(M_NONE), tag, 0u, tag);
        }
      nexth = bh + 1;
      if (last) break;
      if (++f == 2) { f = 0; ph ^= 1; }
    }
    if (lane == 0) TS(11);
    return;
  }

  {
    const int g = lane >> 2, t = lane & 3, mi = lane >> 3, ri = lane & 7;
    const uint32_t kofs = (warp * 16 + (mi & 1) * 8 + ri) * 256 + (mi >> 1) * 128;
    const uint32_t vofs = (warp * 16 + (mi >> 1) * 8 + ri) * 256 + (mi & 1) * 128 + TILE;
    const float sc = 0.08838834764831845f * 1.4426950408889634f;
    uint32_t q0[8], q1[8];
    float m = -INFINITY, l = 0.f;
    float o[2][4];
    unsigned cur = 0xffffu, nun = 0, seq = 0, slot = 0, ph = 0, f = 0, fph = 1;
    bool qall = false;
    const int cm = g ^ (2 * t);
    bool dry = P_DRY & 1;
    if (!dry) mbar_wait(sb + B_Q0, 0);
    while (true) {
      if (!dry) mbar_wait(sb + B_FULL + 16 * slot, ph);
      const unsigned inf = lds32v(sb + SM_INFO + 4 * slot) & 0xffffu;
      if (inf != cur) {
        if (inf & INF_END) break;
        cur = inf;
        const unsigned bh = inf & 0xffu;
        if (bh >= 2 && !qall) { mbar_wait(sb + B_Q1, 0); qall = true; }
#pragma unroll
        for (int c = 0; c < 8; c++) {
          q0[c] = lds32(sb + SM_Q + bh * 256 + ((c ^ g) << 4) + t * 4);
          q1[c] = lds32(sb + SM_Q + bh * 256 + 128 + ((c ^ g) << 4) + t * 4);
        }
        m = -INFINITY; l = 0.f; nun = 0;
#pragma unroll
        for (int i = 0; i < 4; i++) { o[0][i] = 0.f; o[1][i] = 0.f; }
      }
      const uint32_t st = sb + slot * (2 * TILE);
      float s[2][4];
#pragma unroll
      for (int i = 0; i < 4; i++) { s[0][i] = 0.f; s[1][i] = 0.f; }
#pragma unroll
      for (int c = 0; c < 8; c++) {
        uint32_t a0, a1, a2, a3;
        ldsm4(st + kofs + ((c ^ ri) << 4), a0, a1, a2, a3);
        mma16816(s[c & 1], a0, a1, a2, a3, q0[c], q1[c]);
      }
      const float s0 = __shfl_sync(~0u, s[0][0] + s[1][0], 9 * t);
      const float s1 = __shfl_sync(~0u, s[0][1] + s[1][1], 9 * t + 4);
      const float s2 = __shfl_sync(~0u, s[0][2] + s[1][2], 9 * t);
      const float s3 = __shfl_sync(~0u, s[0][3] + s[1][3], 9 * t + 4);
      if (lane == 0 && !dry) mbar_arrive(sb + B_EMPTY + 16 * slot);
      float mx = fmaxf(fmaxf(s0, s1), fmaxf(s2, s3));
      mx = fmaxf(mx, __shfl_xor_sync(~0u, mx, 1));
      mx = fmaxf(mx, __shfl_xor_sync(~0u, mx, 2));
      const float mn = fmaxf(m, mx * sc);
      const float alpha = ex2(m - mn);
      m = mn;
      const float p0 = ex2(fmaf(s0, sc, -mn)), p1 = ex2(fmaf(s1, sc, -mn));
      const float p2 = ex2(fmaf(s2, sc, -mn)), p3 = ex2(fmaf(s3, sc, -mn));
      l = fmaf(l, alpha, (p0 + p1) + (p2 + p3));
      const uint32_t pb0 = pack_bf16(p0, p1), pb1 = pack_bf16(p2, p3);
#pragma unroll
      for (int i = 0; i < 4; i++) { o[0][i] *= alpha; o[1][i] *= alpha; }
      if ((cur & INF_FINAL) && nun == FIN - 1) {
        float lr = l + __shfl_xor_sync(~0u, l, 1);
        lr += __shfl_xor_sync(~0u, lr, 2);
        if (lane < 2)
          st_async64(mapa(sb + SM_XS + ((cta & 1) * 4 + warp) * 272 + 256, lane), __float_as_uint(m), __float_as_uint(lr),
                     mapa(sb + B_X0, lane));
      }
      if (!dry) mbar_wait(sb + B_FULL + 16 * slot + 8, ph);
#pragma unroll
      for (int c = 0; c < 8; c++) {
        uint32_t a0, a1, a2, a3;
        ldsm4t(st + vofs + ((c ^ ri) << 4), a0, a1, a2, a3);
        const uint32_t msk = (c == cm) ? 0x0000ffffu : ((c == (cm ^ 1)) ? 0xffff0000u : 0u);
        mma16816(o[c & 1], a0, a1, a2, a3, pb0 & msk, pb1 & msk);
      }
      if (dry) { dry = false; cur = 0xffffu; mbar_wait(sb + B_Q0, 0); continue; }
      nun++;
      seq++;
      if (cur & INF_FINAL) {
        if (nun == FIN) break;
        __syncwarp();
        if (lane == 0) mbar_arrive(sb + B_EMPTY + 16 * slot + 8);
        if (++slot == NSLOT) { slot = 0; ph ^= 1; }
        continue;
      }
      __syncwarp();
      if (lane == 0) mbar_arrive(sb + B_EMPTY + 16 * slot + 8);
      if (++slot == NSLOT) { slot = 0; ph ^= 1; }
      unsigned nx = lds32v(sb + SM_INFO + 4 * slot);
      if ((nx >> 16) != (seq & 0xffffu)) {
        mbar_wait(sb + B_FULL + 16 * slot, ph);
        nx = lds32v(sb + SM_INFO + 4 * slot);
      }
      nx &= 0xffffu;
      if (nx != cur) {
        float lr = l + __shfl_xor_sync(~0u, l, 1);
        lr += __shfl_xor_sync(~0u, lr, 2);
        mbar_wait(sb + B_FLE + 8 * f, fph);
        const uint32_t base = sb + SM_FL + f * (4 * 528) + warp * 528;
        sts128(base + lane * 16, __float_as_uint(o[0][0] + o[1][0]), __float_as_uint(o[0][1] + o[1][1]),
               __float_as_uint(o[0][2] + o[1][2]), __float_as_uint(o[0][3] + o[1][3]));
        if (lane == 0) sts128(base + 512, __float_as_uint(m), __float_as_uint(lr), cur | (nx & 0x300u), nun);
        __syncwarp();
        if (lane == 0) mbar_arrive(sb + B_FLF + 8 * f);
        if (++f == 2) { f = 0; fph ^= 1; }
      }
    }
    if (owner) {
      const uint32_t v0 = pack_bf16(o[0][0] + o[1][0], o[0][1] + o[1][1]), v1 = pack_bf16(o[0][2] + o[1][2], o[0][3] + o[1][3]);
      const uint32_t dst = sb + SM_XS + ((cta & 1) * 4 + warp) * 272;
#pragma unroll
      for (int rk = 0; rk < 2; rk++) {
        const uint32_t rr = (cta & 1) ^ (rk ^ 1);
        const uint32_t d = mapa(dst, rr), bx = mapa(sb + B_X, rr);
        st_async64(d + lane * 8, v0, v1, bx);
      }
      if (tid == 0) TS(12);
    }
  }
  return;
  }

  {
    asm volatile("barrier.cluster.arrive.relaxed.aligned;" ::: "memory");
    asm volatile("bar.sync 2, 96;" ::: "memory");
    if (lane == 0) {
      unsigned grab = cta - NCTA;
      unsigned seq = 1, slot = 1, ph = 1;
      unsigned ls = 0, lph = 0;
      int fin_left = owner ? FIN : 0;
      bool sweeping = true;
      unsigned wake = owner ? ((cta >> 1) + 1) * SW : 0xffffffffu;
      unsigned wake2 = 12 * SW, wake3 = P_W0 * SW + ((cta >> 1) & 31) * (P_PS * SW / 4);
      int infl = 2, lim = P_L0;
      while (true) {
        unsigned inf;
        size_t off;
        if (sweeping) {
          const unsigned u = grab + (unsigned)(NSTATIC * NCTA);
          if (u >= wake) { mbar_arrive(sb + B_W); wake = 0xffffffffu; }
          if (u >= wake3) { mbar_arrive(sb + B_W3); wake3 = 0xffffffffu; }
          if (u >= wake2) { mbar_arrive(sb + B_W2); wake2 = 0xffffffffu; }
          if (u < (unsigned)SWU) {
            grab = grab_next(sc_->grab);
            const unsigned bh = u / SW;
            off = (size_t)(u + bh * (2 * FIN)) * TILE;
            inf = bh;
          } else {
            sweeping = false;
            lim = P_DF + (P_RK * (u - SWU)) / NCTA;
            TS(10);
          }
        }
        if (!sweeping) {
          if (fin_left == 0) break;
          fin_left--;
          off = (size_t)((cta >> 1) * UPH + SW + 2 * (FIN - 1 - fin_left) + (cta & 1)) * TILE;
          inf = (cta >> 1) | INF_FINAL;
        }
        mbar_wait_n(sb + B_EMPTY + 16 * slot, ph);
        sts32v(sb + SM_INFO + 4 * slot, (seq << 16) | inf);
        while (infl >= lim) {
          mbar_wait_n(sb + B_FULL + 8 * ls, lph);
          if (++ls == NST) { ls = 0; lph ^= 1; }
          infl--;
        }
        infl++;
        mbar_expect_tx(sb + B_FULL + 16 * slot, TILE);
        bulk_load(sb + (2 * slot) * TILE, Kc + off, TILE, sb + B_FULL + 16 * slot, pol);
        if (P_L0 != DEPTH && sweeping) lim = DEPTH;
        mbar_wait_n(sb + B_EMPTY + 16 * slot + 8, ph);
        while (infl >= lim) {
          mbar_wait_n(sb + B_FULL + 8 * ls, lph);
          if (++ls == NST) { ls = 0; lph ^= 1; }
          infl--;
        }
        infl++;
        mbar_expect_tx(sb + B_FULL + 16 * slot + 8, TILE);
        bulk_load(sb + (2 * slot + 1) * TILE, Vc + off, TILE, sb + B_FULL + 16 * slot + 8, pol);
        seq++;
        if (++slot == NSLOT) { slot = 0; ph ^= 1; }
      }
      if (!owner) {
        mbar_wait_n(sb + B_EMPTY + 16 * slot, ph);
        sts32v(sb + SM_INFO + 4 * slot, (seq << 16) | INF_END);
        mbar_arrive(sb + B_FULL + 16 * slot);
      }
    }
    __syncwarp();
    asm volatile("barrier.cluster.wait.acquire.aligned;" ::: "memory");
  }
}

}

extern "C" void kernel_launch(void* const* d_in, const int* in_sizes, int n_in, void* d_out, int out_size) {
  (void)in_sizes; (void)n_in; (void)out_size;
  static bool configured = false;
  static void* scratch = nullptr;
  if (!configured) {
    cudaGetSymbolAddress(&scratch, g_scratch);
    cudaFuncSetAttribute(fused_decode_kernel, cudaFuncAttributeMaxDynamicSharedMemorySize, SM_TOTAL);
    configured = true;
  }
  fused_decode_kernel<<<NCTA, NTHR, SM_TOTAL, cudaStreamPerThread>>>(
      (const char*)d_in[1], (const char*)d_in[2], (Scratch*)scratch, (const __nv_bfloat16*)d_in[0], (const __nv_bfloat16*)d_in[3],
      (const __nv_bfloat16*)d_in[4], (const __nv_bfloat16*)d_in[6], (const __nv_bfloat16*)d_in[7],
      (const __nv_bfloat16*)d_in[8], (const __nv_bfloat16*)d_in[9], (__nv_bfloat16*)d_out);
}
```
